```python
import torch

def _softmax(x, axis=-1):
    return torch.softmax(x, dim=axis)

def _gelu(x):
    return torch.nn.functional.gelu(x, approximate='tanh')

def _silu(x):
    return torch.nn.functional.silu(x)

def _sigmoid(x):
    return torch.sigmoid(x)

def _layernorm(x, axis=-1, eps=1e-05):
    m = x.mean(dim=axis, keepdim=True)
    v = x.var(dim=axis, keepdim=True, unbiased=False)
    return (x - m) / torch.sqrt(v + eps)

def _scatter_add(tgt, idx, src, axis=0):
    return tgt.clone().index_add_(axis, idx, src)

def _segment_sum(src, seg, n):
    out = torch.zeros((n,) + src.shape[1:], dtype=src.dtype)
    return out.index_add_(0, seg, src)

def _pad(x, pw):
    flat = tuple((v for pair in reversed(pw) for v in pair))
    return torch.nn.functional.pad(x, flat)
kernel_name = 'gated_mix__memory_aug_recurrent_mem_tr__linear_attn_block__prompt'

def setup_inputs():

    _w = lambda a: (lambda t: t.to(torch.bfloat16) if t.is_floating_point() else t)(torch.as_tensor(a))

    def _A_setup():
        B, S, Dm = (1, 2048, 512)
        H, Dh = (32, 128)
        M, seg = (8, 32)
        seg = min(seg, S)
        S = S // seg * seg
        return {'x': _w((lambda *s: torch.randn(*s, dtype=torch.bfloat16) * 0.05)(B, S, Dm)), 'mem0': _w((lambda *s: torch.randn(*s, dtype=torch.bfloat16) * 0.8)(B, M, Dm)), 'Wq': _w((lambda *s: torch.randn(*s, dtype=torch.bfloat16) * 1.6)(Dm, H, Dh) * Dm ** (-0.5)), 'Wk': _w((lambda *s: torch.randn(*s, dtype=torch.bfloat16) * 1.6)(Dm, H, Dh) * Dm ** (-0.5)), 'Wv': _w((lambda *s: torch.randn(*s, dtype=torch.bfloat16) * 0.8)(Dm, H, Dh) * Dm ** (-0.5)), 'Wo': _w((lambda *s: torch.randn(*s, dtype=torch.bfloat16) * 0.8)(H, Dh, Dm) * (H * Dh) ** (-0.5)), 'seg_len': seg}
    _A_in = _A_setup()

    def _B_setup():
        B, S, D = (1, 2048, 512)
        return {'x': _w((lambda *s: torch.randn(*s, dtype=torch.bfloat16) * 0.05)(B, S, D)), 'wqkv': _w((lambda *s: torch.randn(*s, dtype=torch.bfloat16) * 1.6)(D, 3 * D)), 'wo': _w((lambda *s: torch.randn(*s, dtype=torch.bfloat16) * 0.1)(D, D))}
    _B_in = _B_setup()
    return {'A_x': _A_in['x'], 'A_mem0': _A_in['mem0'], 'A_Wq': _A_in['Wq'], 'A_Wk': _A_in['Wk'], 'A_Wv': _A_in['Wv'], 'A_Wo': _A_in['Wo'], 'A_seg_len': _A_in['seg_len'], 'B_x': _B_in['x'], 'B_wqkv': _B_in['wqkv'], 'B_wo': _B_in['wo'], 'gate_w': _w((lambda *s: torch.randn(*s, dtype=torch.bfloat16) * 0.05)(512) * 16.0)}

def reference(A_x, A_mem0, A_Wq, A_Wk, A_Wv, A_Wo, A_seg_len, B_x, B_wqkv, B_wo, gate_w):

    def _A_ref(x, mem0, Wq, Wk, Wv, Wo, seg_len):
        B, S, Dm = x.shape
        H, Dh = (Wq.shape[1], Wq.shape[2])
        M = mem0.shape[1]
        scale = Dh ** (-0.5)
        n_seg = S // seg_len
        L = M + seg_len
        idx = torch.arange(L)
        mask = (idx[:, None] < M) | (idx[:, None] >= idx[None, :])
        mem = mem0
        outs = []
        for s in range(n_seg):
            xs = x[:, s * seg_len:(s + 1) * seg_len, :].clone()
            h = torch.concatenate([mem, xs], axis=1)
            q = torch.einsum('btd,dhe->bhte', h, Wq)
            k = torch.einsum('btd,dhe->bhte', h, Wk)
            v = torch.einsum('btd,dhe->bhte', h, Wv)
            scores = torch.einsum('bhqe,bhke->bhqk', q, k) * scale
            scores = torch.where(mask[None, None], scores, -1000000000.0)
            p = _softmax(scores, axis=-1)
            o = torch.einsum('bhqk,bhke->bhqe', p, v)
            o = torch.einsum('bhte,hed->btd', o, Wo)
            mem = o[:, :M, :].clone()
            outs.append(o[:, M:, :])
        return torch.concatenate(outs, axis=1)

    def _B_ref(x, wqkv, wo):
        B, S, D = x.shape
        H = 32
        Dh = D // H
        qkv = (lambda x, *d: x.permute(*d))((x @ wqkv).reshape(B, S, 3, H, Dh), 2, 0, 3, 1, 4)
        q, k, v = (qkv[0], qkv[1], qkv[2])
        phi = lambda t: torch.where(t > 0, t + 1, torch.exp(t)) + 1e-06
        pq, pk = (phi(q), phi(k))
        kv = torch.einsum('bhsd,bhse->bhde', pk, v)
        z = torch.einsum('bhsd->bhd', pk)
        num = torch.einsum('bhqd,bhde->bhqe', pq, kv)
        den = torch.einsum('bhqd,bhd->bhq', pq, z)[..., None] + 1e-06
        o = num / den
        return (lambda x, *d: x.permute(*d))(o, 0, 2, 1, 3).reshape(B, S, D) @ wo
    x = A_x
    g = _sigmoid((x * gate_w).sum(-1, keepdims=True))
    a = _A_ref(x, A_mem0, A_Wq, A_Wk, A_Wv, A_Wo, A_seg_len)
    b = _B_ref(x, B_wqkv, B_wo)
    return g * a + (1 - g) * b
```

```cpp
#include <cuda_runtime.h>
#include <cuda_bf16.h>
#include <cuda_fp16.h>
#include <cuda.h>
#include <stdint.h>

namespace {

constexpr int kS = 2048, kD = 512, kH = 32, kDH = 128, kNSEG = 64, kHD = kH * kDH;

#define DI __device__ __forceinline__
#define LIKELY(x) __builtin_expect(!!(x), 1)
#define UNLIKELY(x) __builtin_expect(!!(x), 0)
constexpr int kSpinLimit = 1 << 22;

template <class T> DI void spin_guard(T& n) {
    asm volatile("{.reg .pred q; add.u32 %0, %0, 1; setp.gt.u32 q, %0, %1; @q st.shared.u32 [%0], %0;}" : "+r"(n) : "n"(kSpinLimit) : "memory");
}
DI uint32_t smem_u32(const void* p) { return (uint32_t)__cvta_generic_to_shared(p); }
DI uint32_t mapa(uint32_t a, uint32_t rank) { uint32_t r; asm("mapa.shared::cluster.u32 %0, %1, %2;" : "=r"(r) : "r"(a), "r"(rank)); return r; }
DI void mbar_init(uint32_t b, int n) { asm volatile("mbarrier.init.shared::cta.b64 [%0], %1;" :: "r"(b), "r"(n) : "memory"); }
DI void mbar_expect(uint32_t b, int bytes) { asm volatile("mbarrier.arrive.expect_tx.shared::cta.b64 _, [%0], %1;" :: "r"(b), "r"(bytes) : "memory"); }
DI bool mbar_try(uint32_t b, uint32_t parity) {
    uint32_t ok;
    asm volatile("{.reg .pred p; mbarrier.try_wait.parity.shared::cta.b64 p, [%1], %2; selp.u32 %0, 1, 0, p;}"
                 : "=r"(ok) : "r"(b), "r"(parity) : "memory");
    return ok;
}
DI bool mbar_test(uint32_t b, uint32_t parity) {
    uint32_t ok;
    asm volatile("{.reg .pred p; mbarrier.test_wait.parity.shared::cta.b64 p, [%1], %2; selp.u32 %0, 1, 0, p;}"
                 : "=r"(ok) : "r"(b), "r"(parity) : "memory");
    return ok;
}
DI void sched_fence() { asm volatile("pmevent 1;" ::: "memory"); }
DI void mbar_wait(uint32_t b, uint32_t parity) {
    asm volatile("{.reg .pred p, q; .reg .u32 n;\n"
                 "mov.u32 n, 0;\n"
                 "WAIT_LOOP:\n"
                 "mbarrier.try_wait.parity.shared::cta.b64 p, [%0], %1;\n"
                 "add.u32 n, n, 1; setp.gt.u32 q, n, %2; @q st.shared.u32 [n], n;\n"
                 "@!p bra WAIT_LOOP;}"
                 :: "r"(b), "r"(parity), "n"(kSpinLimit) : "memory");
}
DI void mbar_wait_unless(uint32_t b, uint32_t parity, bool done) {
    asm volatile("{.reg .pred p, q; .reg .u32 n;\n"
                 "setp.ne.u32 p, %3, 0; mov.u32 n, 0;\n"
                 "WAIT_LOOP:\n"
                 "@!p mbarrier.try_wait.parity.shared::cta.b64 p, [%0], %1;\n"
                 "setp.gt.u32 q, n, %2; add.u32 n, n, 1; or.pred q, q, p;\n"
                 "@!q bra WAIT_LOOP;\n"
                 "@!p st.shared.u32 [n], n;}"
                 :: "r"(b), "r"(parity), "n"(kSpinLimit - 1), "r"((uint32_t)done) : "memory");
}
DI void mbar_wait1(uint32_t b, uint32_t parity) {
    int n = 0;
    while (!mbar_try(b, parity)) spin_guard(n);
}
template <int ID, int N> DI void bar_sync() { asm volatile("bar.sync %0, %1;" :: "n"(ID), "n"(N) : "memory"); }
template <int ID, int N> DI void bar_arrive() { asm volatile("bar.arrive %0, %1;" :: "n"(ID), "n"(N) : "memory"); }
DI void cluster_sync() { asm volatile("barrier.cluster.arrive.aligned; barrier.cluster.wait.aligned;" ::: "memory"); }

DI void ldsm4(uint32_t (&r)[4], uint32_t a) {
    asm volatile("ldmatrix.sync.aligned.m8n8.x4.shared.b16 {%0,%1,%2,%3}, [%4];" : "=r"(r[0]), "=r"(r[1]), "=r"(r[2]), "=r"(r[3]) : "r"(a) : "memory");
}
DI void ldsm4t(uint32_t (&r)[4], uint32_t a) {
    asm volatile("ldmatrix.sync.aligned.m8n8.x4.trans.shared.b16 {%0,%1,%2,%3}, [%4];" : "=r"(r[0]), "=r"(r[1]), "=r"(r[2]), "=r"(r[3]) : "r"(a) : "memory");
}
DI void mma16(float (&c)[4], uint32_t a0, uint32_t a1, uint32_t a2, uint32_t a3, uint32_t b0, uint32_t b1) {
    asm("mma.sync.aligned.m16n8k16.row.col.f32.bf16.bf16.f32 {%0,%1,%2,%3}, {%4,%5,%6,%7}, {%8,%9}, {%0,%1,%2,%3};"
        : "+f"(c[0]), "+f"(c[1]), "+f"(c[2]), "+f"(c[3]) : "r"(a0), "r"(a1), "r"(a2), "r"(a3), "r"(b0), "r"(b1));
}
DI void mma16v(float (&c)[4], uint32_t a0, uint32_t a1, uint32_t a2, uint32_t a3, uint32_t b0, uint32_t b1) {
    asm volatile("mma.sync.aligned.m16n8k16.row.col.f32.bf16.bf16.f32 {%0,%1,%2,%3}, {%4,%5,%6,%7}, {%8,%9}, {%0,%1,%2,%3};"
        : "+f"(c[0]), "+f"(c[1]), "+f"(c[2]), "+f"(c[3]) : "r"(a0), "r"(a1), "r"(a2), "r"(a3), "r"(b0), "r"(b1));
}
DI void mma8v(float (&c)[4], uint32_t a0, uint32_t a1, uint32_t b0) {
    asm volatile("mma.sync.aligned.m16n8k8.row.col.f32.bf16.bf16.f32 {%0,%1,%2,%3}, {%4,%5}, {%6}, {%0,%1,%2,%3};"
        : "+f"(c[0]), "+f"(c[1]), "+f"(c[2]), "+f"(c[3]) : "r"(a0), "r"(a1), "r"(b0));
}
DI float ex2v(float x) { float y; asm volatile("ex2.approx.ftz.f32 %0, %1;" : "=f"(y) : "f"(x)); return y; }
constexpr uint32_t kOnes = 0x3F803F80u;
DI uint32_t pack_bf16(float lo, float hi) { uint32_t r; asm("cvt.rn.bf16x2.f32 %0, %1, %2;" : "=r"(r) : "f"(hi), "f"(lo)); return r; }
DI float ex2(float x) { float y; asm("ex2.approx.ftz.f32 %0, %1;" : "=f"(y) : "f"(x)); return y; }
DI float rcp(float x) { float y; asm("rcp.approx.ftz.f32 %0, %1;" : "=f"(y) : "f"(x)); return y; }

DI void sts32(uint32_t a, uint32_t v) { asm volatile("st.shared.b32 [%0], %1;" :: "r"(a), "r"(v) : "memory"); }
DI void sts64f(uint32_t a, float x, float y) { asm volatile("st.shared.v2.f32 [%0], {%1,%2};" :: "r"(a), "f"(x), "f"(y) : "memory"); }
DI void sts128f(uint32_t a, float x, float y, float z, float w) { asm volatile("st.shared.v4.f32 [%0], {%1,%2,%3,%4};" :: "r"(a), "f"(x), "f"(y), "f"(z), "f"(w) : "memory"); }
DI void sts128(uint32_t a, uint32_t x, uint32_t y, uint32_t z, uint32_t w) { asm volatile("st.shared.v4.b32 [%0], {%1,%2,%3,%4};" :: "r"(a), "r"(x), "r"(y), "r"(z), "r"(w) : "memory"); }
DI float4 lds128f(uint32_t a) { float4 v; asm volatile("ld.shared.v4.f32 {%0,%1,%2,%3}, [%4];" : "=f"(v.x), "=f"(v.y), "=f"(v.z), "=f"(v.w) : "r"(a) : "memory"); return v; }
DI void lds128(uint32_t (&r)[4], uint32_t a) { asm volatile("ld.shared.v4.b32 {%0,%1,%2,%3}, [%4];" : "=r"(r[0]), "=r"(r[1]), "=r"(r[2]), "=r"(r[3]) : "r"(a) : "memory"); }

DI uint32_t adr(uint32_t l, uint32_t u) { uint32_t r; asm volatile("add.u32 %0, %1, %2;" : "=r"(r) : "r"(l), "r"(u)); return r; }
DI void st_async32(uint32_t a, uint32_t v, uint32_t bar) {
    asm volatile("st.async.shared::cluster.mbarrier::complete_tx::bytes.b32 [%0], %1, [%2];" :: "r"(a), "r"(v), "r"(bar) : "memory");
}
DI void bulk_s2s(uint32_t dst, uint32_t src, int bytes, uint32_t bar) {
    asm volatile("cp.async.bulk.shared::cluster.shared::cta.mbarrier::complete_tx::bytes [%0], [%1], %2, [%3];"
                 :: "r"(dst), "r"(src), "r"(bytes), "r"(bar) : "memory");
}
DI void mbar_arrive(uint32_t b) { asm volatile("mbarrier.arrive.shared::cta.b64 _, [%0];" :: "r"(b) : "memory"); }
DI void fence_async() { asm volatile("fence.proxy.async.shared::cta;" ::: "memory"); }
DI void red_h128(void* p, uint32_t a, uint32_t b, uint32_t c, uint32_t d) {
    asm volatile("red.relaxed.gpu.global.add.noftz.v4.f16x2 [%0], {%1,%2,%3,%4};" :: "l"(p), "r"(a), "r"(b), "r"(c), "r"(d) : "memory");
}
DI void red_h64(void* p, uint32_t a, uint32_t b) {
    asm volatile("red.relaxed.gpu.global.add.noftz.v2.f16x2 [%0], {%1,%2};" :: "l"(p), "r"(a), "r"(b) : "memory");
}
DI uint2 ld_relaxed64(const void* p) {
    uint2 v;
    asm volatile("ld.relaxed.gpu.global.v2.u32 {%0,%1}, [%2];" : "=r"(v.x), "=r"(v.y) : "l"(p) : "memory");
    return v;
}
DI uint32_t pack_f16(float lo, float hi) { uint32_t r; asm("cvt.rn.f16x2.f32 %0, %1, %2;" : "=r"(r) : "f"(hi), "f"(lo)); return r; }
DI uint32_t f16x2_to_bf16x2(uint32_t w) {
    float lo, hi;
    asm("{.reg .f16 a, b; mov.b32 {a, b}, %2; cvt.f32.f16 %0, a; cvt.f32.f16 %1, b;}" : "=f"(lo), "=f"(hi) : "r"(w));
    return pack_bf16(lo, hi);
}
DI uint32_t absmax2(uint32_t m, uint32_t w) { return __vmaxu2(m, w & 0x7FFF7FFFu); }
DI uint32_t hfma2_sq(uint32_t w, uint32_t c) { uint32_t r; asm("fma.rn.bf16x2 %0, %1, %1, %2;" : "=r"(r) : "r"(w), "r"(c)); return r; }
DI float sumsq8(const uint32_t (&f)[4], const uint32_t (&g)[4]) {
    uint32_t q = 0;
#pragma unroll
    for (int i = 0; i < 4; i++) q = hfma2_sq(g[i], hfma2_sq(f[i], q));
    return __uint_as_float(q << 16) + __uint_as_float(q & 0xFFFF0000u);
}
DI void stsm4(uint32_t a, uint32_t x, uint32_t y, uint32_t z, uint32_t w) {
    asm volatile("stmatrix.sync.aligned.m8n8.x4.shared.b16 [%0], {%1,%2,%3,%4};" :: "r"(a), "r"(x), "r"(y), "r"(z), "r"(w) : "memory");
}
DI void mbar_arrive_if(uint32_t b, bool p) {
    asm volatile("{.reg .pred p; setp.ne.u32 p, %1, 0; @p mbarrier.arrive.shared::cta.b64 _, [%0];}" :: "r"(b), "r"((uint32_t)p) : "memory");
}
DI uint4 ld_relaxed128(const void* p) {
    uint4 v;
    asm volatile("ld.relaxed.gpu.global.v4.u32 {%0,%1,%2,%3}, [%4];" : "=r"(v.x), "=r"(v.y), "=r"(v.z), "=r"(v.w) : "l"(p) : "memory");
    return v;
}
DI uint32_t lds32(uint32_t a) { uint32_t v; asm volatile("ld.shared.b32 %0, [%1];" : "=r"(v) : "r"(a) : "memory"); return v; }
DI uint32_t clk32() { unsigned long long c; asm volatile("mov.u64 %0, %%clock64;" : "=l"(c) :: "memory"); return (uint32_t)c; }
DI void wait_until(uint32_t t) { while ((int)(clk32() - t) < 0) {} }

DI void tma2d(uint32_t dst, const CUtensorMap* m, int c0, int c1, uint32_t bar) {
    asm volatile("cp.async.bulk.tensor.2d.shared::cluster.global.mbarrier::complete_tx::bytes [%0], [%1, {%3, %4}], [%2];"
                 :: "r"(dst), "l"(m), "r"(bar), "r"(c0), "r"(c1) : "memory");
}
DI void tma5d_mc(uint32_t dst, const CUtensorMap* m, int c0, int c4, uint32_t bar, uint16_t mask) {
    asm volatile("cp.async.bulk.tensor.5d.shared::cluster.global.mbarrier::complete_tx::bytes.multicast::cluster [%0], [%1, {%3, %5, %5, %5, %4}], [%2], %6;"
                 :: "r"(dst), "l"(m), "r"(bar), "r"(c0), "r"(c4), "r"(0), "h"(mask) : "memory");
}
DI void wgmma_fence() { asm volatile("wgmma.fence.sync.aligned;" ::: "memory"); }
DI void wgmma_commit() { asm volatile("wgmma.commit_group.sync.aligned;" ::: "memory"); }
template <int N> DI void wgmma_wait() { asm volatile("wgmma.wait_group.sync.aligned %0;" :: "n"(N) : "memory"); }
template <int ACC> DI void wgmma_rs32(float (&d)[16], uint32_t a0, uint32_t a1, uint32_t a2, uint32_t a3, uint64_t desc) {
    asm volatile("{.reg .pred p; setp.ne.b32 p, %21, 0;\n"
                 "wgmma.mma_async.sync.aligned.m64n32k16.f32.bf16.bf16 {%0,%1,%2,%3,%4,%5,%6,%7,%8,%9,%10,%11,%12,%13,%14,%15}, {%16,%17,%18,%19}, %20, p, 1, 1, 0;}"
                 : "+f"(d[0]), "+f"(d[1]), "+f"(d[2]), "+f"(d[3]), "+f"(d[4]), "+f"(d[5]), "+f"(d[6]), "+f"(d[7]),
                   "+f"(d[8]), "+f"(d[9]), "+f"(d[10]), "+f"(d[11]), "+f"(d[12]), "+f"(d[13]), "+f"(d[14]), "+f"(d[15])
                 : "r"(a0), "r"(a1), "r"(a2), "r"(a3), "l"(desc), "n"(ACC));
}
DI void wgmma_rs32_first(float (&d)[16], uint32_t a0, uint32_t a1, uint32_t a2, uint32_t a3, uint64_t desc) {
    asm volatile("{.reg .pred p; setp.ne.b32 p, 0, 0;\n"
                 "wgmma.mma_async.sync.aligned.m64n32k16.f32.bf16.bf16 {%0,%1,%2,%3,%4,%5,%6,%7,%8,%9,%10,%11,%12,%13,%14,%15}, {%16,%17,%18,%19}, %20, p, 1, 1, 0;}"
                 : "=f"(d[0]), "=f"(d[1]), "=f"(d[2]), "=f"(d[3]), "=f"(d[4]), "=f"(d[5]), "=f"(d[6]), "=f"(d[7]),
                   "=f"(d[8]), "=f"(d[9]), "=f"(d[10]), "=f"(d[11]), "=f"(d[12]), "=f"(d[13]), "=f"(d[14]), "=f"(d[15])
                 : "r"(a0), "r"(a1), "r"(a2), "r"(a3), "l"(desc));
}
template <int FIRST> DI void wgmma_ss32(float (&d)[16], uint64_t da, uint64_t db) {
    if (FIRST)
        asm volatile("{.reg .pred p; setp.ne.b32 p, 0, 0;\n"
                     "wgmma.mma_async.sync.aligned.m64n32k16.f32.bf16.bf16 {%0,%1,%2,%3,%4,%5,%6,%7,%8,%9,%10,%11,%12,%13,%14,%15}, %16, %17, p, 1, 1, 1, 0;}"
                     : "=f"(d[0]), "=f"(d[1]), "=f"(d[2]), "=f"(d[3]), "=f"(d[4]), "=f"(d[5]), "=f"(d[6]), "=f"(d[7]),
                       "=f"(d[8]), "=f"(d[9]), "=f"(d[10]), "=f"(d[11]), "=f"(d[12]), "=f"(d[13]), "=f"(d[14]), "=f"(d[15])
                     : "l"(da), "l"(db));
    else
        asm volatile("{.reg .pred p; setp.eq.b32 p, 0, 0;\n"
                     "wgmma.mma_async.sync.aligned.m64n32k16.f32.bf16.bf16 {%0,%1,%2,%3,%4,%5,%6,%7,%8,%9,%10,%11,%12,%13,%14,%15}, %16, %17, p, 1, 1, 1, 0;}"
                     : "+f"(d[0]), "+f"(d[1]), "+f"(d[2]), "+f"(d[3]), "+f"(d[4]), "+f"(d[5]), "+f"(d[6]), "+f"(d[7]),
                       "+f"(d[8]), "+f"(d[9]), "+f"(d[10]), "+f"(d[11]), "+f"(d[12]), "+f"(d[13]), "+f"(d[14]), "+f"(d[15])
                     : "l"(da), "l"(db));
}
DI uint64_t desc_k128(uint32_t addr16) {
    uint64_t d;
    asm("mov.b64 %0, {%1, %2};" : "=l"(d) : "r"(addr16), "n"(0x40000040));
    return d;
}

#define KLINE 1024
constexpr int kLine = KLINE, kBlkBytes = 6 * kLine;
__device__ __align__(1024) char g_ring_mem[384 * kLine];
__device__ uint2 g_stat[96];
DI int slot_off(int s) { return (s & 1) * 128 + (s & 2) * 256; }
__device__ unsigned g_ctr[32];
__device__ __align__(1024) uint32_t g_ts[16 * 256];
__device__ __nv_bfloat16 g_O[kS * kHD];

__device__ __nv_bfloat16 g_qkvT[1536 * kS];
__device__ __nv_bfloat16 g_ob[kS * kD];
__device__ float g_gate[kS];
__device__ float4 g_acc[kS * kD / 4];
__device__ unsigned g_flags[64 + kNSEG * 8 + kNSEG * 4];
#define g_sync (g_flags)
#define g_oflag (g_flags + 64)
#define g_done (g_flags + 64 + kNSEG * 8)

struct Tune { int x[4]; int xt, xp, xx, xq; };
#define STAMP(i) do {} while (0)
#define TL(c, i) do {} while (0)
#define TLS(c, i) do {} while (0)

#define GRP 2
#define GDEP 1
#define SF0 0
#define O_KM 0
#define O_SCH 0
#define O_SCALE 0
#define O_HV 2
#define O_SHF 1
#define O_W0 4
#define O_W1 8
#define O_PV 0
#define O_SF1 0
#define O_T2 0
#define O_T3 0
#define SSPOS 2
#define SSGAP 8
#define O_SEEN 1
#define O_SF2 1
#define O_T2B 0
#define O_R 0
#define O_REL 2
#define O_PIPE 2
#define O_SPLIT 3
#define O_K2 0
#define NQDEF 2
#define NSLEEP 20
#define OPT_END
constexpr int PLANE = 2080;
constexpr int PLB = 4 * PLANE;
constexpr int SLOT = 14 * PLANE;
constexpr int OFF_X = 0;
constexpr int OFF_QM = 65536;
constexpr int OFF_MEMT = OFF_QM + 2048;
constexpr int OFF_SX = OFF_MEMT + 8192;
constexpr int OFF_OX = OFF_SX + 10240;
constexpr int OFF_WST = 32768;
constexpr int OFF_WOST = OFF_WST + 114688;
constexpr int OFF_KV = OFF_OX + 2048;
constexpr int OFF_WO2 = OFF_KV + 3 * SLOT;
constexpr int OFF_OST = (OFF_WO2 + 1023) & ~1023;
constexpr int OFF_DBG = OFF_WO2 + 17408;
constexpr int OFF_WS = OFF_WOST + 65536;
constexpr int OFF_BAR = OFF_WS + 16384;
constexpr int CHAIN_SMEM = OFF_BAR + 224 + 256;
static_assert(OFF_DBG + 4096 <= OFF_WS && OFF_KV + 2 * SLOT <= OFF_WOST && OFF_WO2 >= OFF_WOST, "smem map");
constexpr int BAR_W = 0, BAR_WO = 32, BAR_X = 40, BAR_HOP = 56, BAR_HV = 64, BAR_KVX = 72, BAR_PL = 96, BAR_SENT = 112, BAR_DUMMY = 152, BAR_C = 208,
              OFF_INV = 136, OFF_SCALE = 144, OFF_CW = 148, OFF_WMAX = 160, OFF_XB = 224;

constexpr float kScaleLog2 = 0.08838834764831845f * 1.4426950408889634f;
constexpr float kMaskRaw = -1.0e9f / 0.08838834764831845f;

template <bool B> struct Flag { static constexpr bool value = B; };
DI uint32_t keep(uint32_t v) { return __shfl_sync(~0u, v, threadIdx.x & 31); }

DI uint32_t gtime() { unsigned long long g; asm volatile("mov.u64 %0, %%globaltimer;" : "=l"(g) :: "memory"); return (uint32_t)g; }
DI uint32_t make_stamp(uint32_t g, int s) { return ((g >> 3) & 0xFFFC) | (((s >> 1) + 1) & 3); }
DI uint32_t load_stamps(const uint32_t* p) {
    uint32_t u; asm volatile("ld.relaxed.gpu.global.u32 %0, [%1];" : "=r"(u) : "l"(p) : "memory");
    return u;
}
DI uint32_t latest_stamp(const uint32_t* p, uint32_t u, uint32_t t0, uint32_t g0) {
    int n = 0;
    while (UNLIKELY(!__all_sync(~0u, (((u ^ g0) | ((u >> 16) ^ g0)) & 3) == 0))) { spin_guard(n); u = load_stamps(p); }
    const int d0 = (int)((u - g0) << 16) >> 16, d1 = (int)(((u >> 16) - g0) << 16) >> 16;
    return t0 + min(__reduce_max_sync(~0u, max(d0, d1)), 512) * 14;
}

DI void announce(unsigned* flag, bool p) {
    asm volatile("{.reg .pred p; setp.ne.u32 p, %1, 0; cp.async.bulk.wait_group 0; @p red.relaxed.gpu.global.add.u32 [%0], 1;}"
                 :: "l"(flag), "r"((uint32_t)p) : "memory");
    __syncwarp();
}

template <int G, class F>
DI void x_attention(uint32_t lin, uint32_t par, uint32_t qad, uint32_t xown, uint32_t xoth, int lane, uint32_t ost, F wait_mem,
                    const uint32_t* stamps, uint32_t& seen, bool release) {
    constexpr int NX = 4 - G, NP = NX + 1;
    float sc[NP][4];
    uint32_t q[4][4], kf[NP][2][4], vf[2][4][4], vm[2][4];
#pragma unroll
    for (int kp = 0; kp < 2; kp++) {
        ldsm4t(q[2 * kp], qad + kp * 512);
        ldsm4t(q[2 * kp + 1], qad + kp * 512 + 256);
#pragma unroll
        for (int p = 0; p < NX; p++) ldsm4t(kf[p][kp], lin + p * PLANE + kp * 512);
    }
#pragma unroll
    for (int p = 0; p < NP; p++) { sc[p][0] = sc[p][1] = sc[p][2] = sc[p][3] = 0.f; }
#pragma unroll
    for (int kk = 0; kk < 4; kk++)
#pragma unroll
        for (int p = 0; p < NX; p++) mma16v(sc[p], q[kk][0], q[kk][1], q[kk][2], q[kk][3], kf[p][kk >> 1][(kk & 1) * 2], kf[p][kk >> 1][(kk & 1) * 2 + 1]);
#pragma unroll
    for (int p = 0; p <= G; p++) sts128f(xown + p * 512, sc[p][0], sc[p][1], sc[p][2], sc[p][3]);
    if (G == 0) sts128f(xown + 512, sc[1][2], sc[1][3], sc[2][2], sc[2][3]);
    wait_mem();
    {
        float s2[4] = {};
        ldsm4t(kf[NX][0], lin + 4 * PLANE); ldsm4t(kf[NX][1], lin + 4 * PLANE + 512);
#pragma unroll
        for (int kk = 0; kk < 4; kk++)
            mma16((kk & 1) ? s2 : sc[NX], q[kk][0], q[kk][1], q[kk][2], q[kk][3], kf[NX][kk >> 1][(kk & 1) * 2], kf[NX][kk >> 1][(kk & 1) * 2 + 1]);
#pragma unroll
        for (int i = 0; i < 4; i++) sc[NX][i] += s2[i];
    }
    sts64f(xown + 1024, sc[NX - 1][2], sc[NX - 1][3]);
    sts128f(xown + 1536, sc[NX][0], sc[NX][1], sc[NX][2], sc[NX][3]);
    bar_sync<6 + G, 64>();
    {
        const float4 o0 = lds128f(xoth), o1 = lds128f(xoth + 512), o2 = lds128f(xoth + 1024), o3 = lds128f(xoth + 1536);
        sc[0][0] += o0.x; sc[0][1] += o0.y; sc[0][2] += o0.z; sc[0][3] += o0.w;
        if (G == 0) { sc[1][2] += o1.x; sc[1][3] += o1.y; sc[2][2] += o1.z; sc[2][3] += o1.w; }
        else { sc[1][0] += o1.x; sc[1][1] += o1.y; sc[1][2] += o1.z; sc[1][3] += o1.w; }
        sc[NX - 1][2] += o2.x; sc[NX - 1][3] += o2.y;
        sc[NX][0] += o3.x; sc[NX][1] += o3.y; sc[NX][2] += o3.z; sc[NX][3] += o3.w;
    }
#pragma unroll
    for (int c = 0; c < 2; c++) {
        ldsm4(vm[c], lin + 9 * PLANE + c * 512);
#pragma unroll
        for (int j = 0; j < 4; j++) ldsm4(vf[c][j], par + (5 + (j & 2)) * PLANE + c * 512 + (j & 1) * 256);
    }
    const int g = lane >> 2, t2 = (lane & 3) * 2;
    if (t2 > g) { sc[G][0] = kMaskRaw; sc[NX - 1][2] = kMaskRaw; }
    if (t2 + 1 > g) { sc[G][1] = kMaskRaw; sc[NX - 1][3] = kMaskRaw; }
    float m0 = fmaxf(sc[NX][0], sc[NX][1]), m1 = fmaxf(sc[NX][2], sc[NX][3]);
#pragma unroll
    for (int p = 0; p < NX; p++) {
        if (p <= G) m0 = fmaxf(m0, fmaxf(sc[p][0], sc[p][1]));
        m1 = fmaxf(m1, fmaxf(sc[p][2], sc[p][3]));
    }
    m0 = fmaxf(m0, __shfl_xor_sync(~0u, m0, 1)); m1 = fmaxf(m1, __shfl_xor_sync(~0u, m1, 1));
    m0 = fmaxf(m0, __shfl_xor_sync(~0u, m0, 2)); m1 = fmaxf(m1, __shfl_xor_sync(~0u, m1, 2));
    m0 *= -kScaleLog2; m1 *= -kScaleLog2;
    float s0 = 0.f, s1 = 0.f;
    uint32_t P[5][2] = {};
#pragma unroll
    for (int p = 0; p < NP; p++) {
        uint32_t (&d)[2] = P[p == NX ? 4 : p];
        if (p <= G || p == NX) {
            const float e0 = ex2(fmaf(sc[p][0], kScaleLog2, m0)), e1 = ex2(fmaf(sc[p][1], kScaleLog2, m0));
            s0 += e0 + e1; d[0] = pack_bf16(e0, e1);
        }
        const float e2 = ex2(fmaf(sc[p][2], kScaleLog2, m1)), e3 = ex2(fmaf(sc[p][3], kScaleLog2, m1));
        s1 += e2 + e3; d[1] = pack_bf16(e2, e3);
    }
    seen = load_stamps(stamps);
    float o[2][4][4] = {};
#pragma unroll
    for (int j = 0; j < 2; j++)
#pragma unroll
        for (int c = 0; c < 2; c++)
#pragma unroll
            for (int i = 0; i < 4; i++)
                mma16v(o[c][i], P[2 * j][0], P[2 * j][1], P[2 * j + 1][0], P[2 * j + 1][1], vf[c][2 * j + (i >> 1)][(i & 1) * 2], vf[c][2 * j + (i >> 1)][(i & 1) * 2 + 1]);
#pragma unroll
    for (int c = 0; c < 2; c++)
#pragma unroll
        for (int i = 0; i < 4; i++) mma8v(o[c][i], P[4][0], P[4][1], vm[c][i]);
    sched_fence();
    if (release) bar_arrive<8, 384>();
    sched_fence();
    s0 += __shfl_xor_sync(~0u, s0, 1); s1 += __shfl_xor_sync(~0u, s1, 1);
    s0 += __shfl_xor_sync(~0u, s0, 2); s1 += __shfl_xor_sync(~0u, s1, 2);
    const float i0 = rcp(s0), i1 = rcp(s1);
#pragma unroll
    for (int c = 0; c < 2; c++) {
        const uint32_t d = ost + g * 128 + (((c * 4 + (lane & 3)) ^ g) << 4);
        sts128(d, pack_bf16(o[c][0][0] * i0, o[c][0][1] * i0), pack_bf16(o[c][1][0] * i0, o[c][1][1] * i0),
               pack_bf16(o[c][2][0] * i0, o[c][2][1] * i0), pack_bf16(o[c][3][0] * i0, o[c][3][1] * i0));
        sts128(d + 1024, pack_bf16(o[c][0][2] * i1, o[c][0][3] * i1), pack_bf16(o[c][1][2] * i1, o[c][1][3] * i1),
               pack_bf16(o[c][2][2] * i1, o[c][2][3] * i1), pack_bf16(o[c][3][2] * i1, o[c][3][3] * i1));
    }
}

DI void load_x(uint32_t sb, const CUtensorMap* mapx, uint32_t rank, int n) {
    const int b = n & 1;
    const uint32_t bar = sb + OFF_BAR + BAR_X + 8 * b, dst = sb + OFF_X + b * 32768 + rank * 4096;
    mbar_expect(bar, 32768);
    tma5d_mc(dst, mapx, rank * 64, n, bar, 7);
    tma5d_mc(dst + 3 * 4096, mapx, rank * 64 + 192, n, bar, 7);
    if (rank < 2) tma5d_mc(dst + 6 * 4096, mapx, rank * 64 + 384, n, bar, 7);
}

template <bool HASF, class F>
DI uint32_t stage_blocks(const char* src, const char* src2, uint32_t st, uint32_t sb, int n, F between) {
    uint32_t w[4][4];
    uint32_t spins = 0;
    bool ok;
    do {
        uint4 v[4]; uint2 u[4];
#pragma unroll
        for (int i = 0; i < 4; i++) { v[i] = ld_relaxed128(src + i * kBlkBytes); u[i] = ld_relaxed64(src2 + i * kBlkBytes); }
        if (!O_PIPE || HASF) {
            if (spins == 0) between();
            spin_guard(spins);
            sched_fence();
        } else if (O_PIPE == 2) {
            spin_guard(spins);
        }
        uint32_t bad = 0;
#pragma unroll
        for (int i = 0; i < 4; i++) {
            w[i][0] = f16x2_to_bf16x2(v[i].x); w[i][1] = f16x2_to_bf16x2(v[i].y); w[i][2] = f16x2_to_bf16x2(v[i].z); w[i][3] = f16x2_to_bf16x2(u[i].x);
            stsm4(st + i * 512, w[i][0], w[i][1], w[i][2], w[i][3]);
            if (i + 1 == O_SPLIT && !HASF) {
                sched_fence();
#pragma unroll
                for (int j = 0; j < 4; j++) asm volatile("" : "+r"(v[j].w), "+r"(u[j].y), "+r"(v[j].x), "+r"(v[j].y), "+r"(v[j].z), "+r"(u[j].x));
            }
        }
#pragma unroll
        for (int i = 0; i < 4; i++) bad |= (v[i].w ^ 0x5000u) | (u[i].y ^ 0x5000u);
        if (O_PIPE == 1 && !HASF) spin_guard(spins);
        ok = __all_sync(~0u, bad == 0);
    } while (!ok);
    bar_arrive<1, 384>();
    sched_fence();
    uint32_t m = 0;
#pragma unroll
    for (int i = 0; i < 4; i++) m = absmax2(absmax2(absmax2(absmax2(m, w[i][0]), w[i][1]), w[i][2]), w[i][3]);
    return m;
}
DI void put_max(uint32_t bars, int warp, uint32_t m) {
    sts32(bars + OFF_WMAX + warp * 4, __reduce_max_sync(~0u, max(m & 0xFFFFu, m >> 16)) << 16);
}
DI void next_scale(uint32_t bars, int n, int lane) {
    const uint32_t m = __reduce_max_sync(~0u, lds32(bars + OFF_WMAX + (lane & 3) * 4));
    const float mmax = __uint_as_float(m) * __uint_as_float(lds32(bars + OFF_INV + (n & 1) * 4));
    const float bound = __uint_as_float(lds32(bars + OFF_CW)) * fmaxf(mmax, __uint_as_float(lds32(bars + OFF_XB + n * 4)));
    const uint32_t eb = min(max(__float_as_uint(bound) >> 23, 30u), 240u);
    sts32(bars + OFF_SCALE, (268 - eb) << 23);
    sts32(bars + OFF_INV + ((n + 1) & 1) * 4, (eb - 14) << 23);
}

__global__ void __cluster_dims__(3, 1, 1) __launch_bounds__(384, 1)
chain_kernel(const __grid_constant__ CUtensorMap mapx, const __grid_constant__ CUtensorMap mapq,
             const __grid_constant__ CUtensorMap mapk, const __grid_constant__ CUtensorMap mapv,
             const __grid_constant__ CUtensorMap mapo, const __grid_constant__ CUtensorMap mapos, const __nv_bfloat16* __restrict__ mem0,
             const __nv_bfloat16* __restrict__ xg, char* const g_ring, const __grid_constant__ Tune tune) {
    extern __shared__ __align__(1024) unsigned char smem[];
    const uint32_t sb = smem_u32(smem);
    const uint32_t bars = sb + OFF_BAR;
    const int tid = threadIdx.x, lane = tid & 31;
    const int warp = __reduce_max_sync(~0u, tid >> 5);
    const int head = blockIdx.x / 3;
    uint32_t rank; asm("mov.u32 %0, %%cluster_ctarank;" : "=r"(rank));
    const int kvx_bytes = rank == 1 ? PLB : 2 * PLB;
    const int hop_bytes = rank == 2 ? 2048 + 32 : 2048;
    const uint32_t rA = mapa(sb, rank == 0 ? 1 : 0), rB = mapa(sb, rank == 2 ? 1 : 2);
    const uint32_t own_planes = OFF_KV + (rank == 0 ? 10 : (rank == 1 ? 0 : 5)) * PLANE;

    auto send_planes = [&](int n, int which) {
        const uint32_t o = own_planes + (n % 3) * SLOT, kb = OFF_BAR + BAR_KVX + 8 * (n % 3), r = which ? rB : rA;
        if (which || rank != 0) bulk_s2s(r + o, sb + o, PLB, r + kb);
    };

    uint2 m0[8]; uint4 xs[16];
    if (warp >= 8) {
#pragma unroll
        for (int q = 0; q < 8; q++) m0[q] = __ldg((const uint2*)(mem0 + q * kD) + tid - 256);
#pragma unroll
        for (int i = 0; i < 16; i++) xs[i] = __ldg((const uint4*)(xg + (size_t)(head * 2 + (rank & 1)) * 32 * kD) + tid - 256 + i * 128);
        if (rank == 2) {
            if (warp < 11) *(float4*)(g_ring + slot_off(lane >> 3) + (head * 3 + warp - 8) * kLine + (lane & 7) * 16) = make_float4(0.f, 0.f, 0.f, 0.f);
            else if (lane < 26) g_flags[head * 26 + lane] = 0;
        }
    }
    if (rank != 2) asm volatile("griddepcontrol.launch_dependents;" ::: "memory");
    if (tid == 0) {
        for (int i = 0; i < 4; i++) mbar_init(bars + BAR_W + 8 * i, 1);
        mbar_init(bars + BAR_WO, 1);
        mbar_init(bars + BAR_X, 1); mbar_init(bars + BAR_X + 8, 1);
        mbar_init(bars + BAR_HOP, 1); mbar_init(bars + BAR_SENT, 12); mbar_init(bars + BAR_HV, 1);
        for (int i = 0; i < 3; i++) mbar_init(bars + BAR_KVX + 8 * i, 1);
        mbar_init(bars + BAR_PL, 8); mbar_init(bars + BAR_C, 3); mbar_init(bars + BAR_C + 8, 3);
        for (int i = 0; i < 4; i++) mbar_expect(bars + BAR_W + 8 * i, 32768);
        if (rank < 2) { mbar_expect(bars + BAR_WO, 65536); mbar_expect(bars + BAR_HV, 2048); }
        mbar_expect(bars + BAR_HOP, hop_bytes);
        for (int i = 0; i < 3; i++) mbar_expect(bars + BAR_KVX + 8 * i, kvx_bytes);
        sts32(bars + OFF_INV, __float_as_uint(1.f));
        asm volatile("fence.mbarrier_init.release.cluster;" ::: "memory");
        TL(blockIdx.x, 0);
    }
    __syncthreads();
    asm volatile("barrier.cluster.arrive.relaxed.aligned;" ::: "memory");
    const uint32_t tstart = clk32();
    if (lane == 0 && warp >= 8 && rank < 2) {
        const int i = warp - 8;
        tma2d(sb + OFF_WOST + i * 16384, &mapo, (i >> 1) * 256 + rank * 128 + (i & 1) * 64, head * kDH, bars + BAR_WO);
    }
    __syncwarp();
    asm volatile("barrier.cluster.wait.aligned;" ::: "memory");
    if (tid == 0) { load_x(sb, &mapx, rank, 0); TL(blockIdx.x, 13); }
    __syncwarp();

    if (warp < 8) {
        asm volatile("setmaxnreg.dec.sync.aligned.u32 160;");
        {
            if (rank < 2) wait_until(tstart + tune.xx);
            if (lane == 0) {
                const CUtensorMap* mw = rank == 0 ? &mapq : (rank == 1 ? &mapk : &mapv);
                for (int i = warp; i < 16; i += 8)
                    tma2d(sb + (i < 2 ? OFF_WS : OFF_WST - 16384) + i * 8192, mw, head * kDH + (i & 1) * 64, (i >> 1) * 64, bars + BAR_W + 8 * ((i >> 3) * 2 + (i & 1)));
            }
            __syncwarp();
        }
        uint32_t W[28][4], ws[4][4];
        const uint32_t wrel = ((warp >> 2) * 8192 + ((lane >> 4) * 8 + (lane & 7)) * 128 + ((((warp & 3) * 2 + ((lane >> 3) & 1)) ^ (lane & 7)) << 4));
        float ss = 0.f;
        {
            mbar_wait(bars + BAR_W + 8 * (warp >> 2), 0);
#pragma unroll
            for (int kk = 0; kk < 4; kk++) ldsm4t(ws[kk], wrel + (sb + OFF_WS + kk * 2048));
#pragma unroll
            for (int kk = 0; kk < 12; kk++) ldsm4t(W[kk], wrel + (sb + OFF_WST + (kk >> 2) * 16384 + (kk & 3) * 2048));
            if (rank == 2) {
                ss = sumsq8(ws[0], ws[1]) + sumsq8(ws[2], ws[3]);
#pragma unroll
                for (int kk = 0; kk < 12; kk += 2) ss += sumsq8(W[kk], W[kk + 1]);
                asm volatile("" : "+f"(ss));
            }
            mbar_wait(bars + BAR_W + 16 + 8 * (warp >> 2), 0);
#pragma unroll
            for (int kk = 12; kk < 28; kk++) ldsm4t(W[kk], wrel + (sb + OFF_WST + (kk >> 2) * 16384 + (kk & 3) * 2048));
        }
        if (tid == 0) TL(blockIdx.x, 1);
        asm volatile("" :: "r"(W[11][3]), "r"(W[27][3]) : "memory");
        auto cluster_signal = [&](int i) {
            bar_sync<2, 256>();
            if (tid < 3) asm volatile("mbarrier.arrive.relaxed.cluster.shared::cluster.b64 _, [%0];" :: "r"(mapa(bars + BAR_C + 8 * i, tid)) : "memory");
            __syncwarp();
        };
        cluster_signal(0);
        if (rank == 2) {
#pragma unroll
            for (int kk = 12; kk < 28; kk += 2) ss += sumsq8(W[kk], W[kk + 1]);
#pragma unroll
            for (int o = 16; o; o >>= 1) ss += __shfl_xor_sync(~0u, ss, o);
            sts32(bars + OFF_XB + warp * 4, __float_as_uint(ss));
            bar_arrive<3, 384>();
        }
        if (warp == 7) {
            mbar_wait(bars + BAR_C, 0);
            if (lane == 0) load_x(sb, &mapx, rank, 1);
            __syncwarp();
        }
        if (tid == 0) TL(blockIdx.x, 2);

        const uint32_t lin = keep(lane * 16);
        uint32_t mdst = keep((16 * warp + (lane >> 2)) * 16 + (lane & 3) * 4 + (rank == 0 ? OFF_QM : own_planes + 4 * PLANE));
        const uint32_t hbar = OFF_BAR + (rank == 2 ? BAR_HV : BAR_HOP);
        const bool lead = lin == 0;
        const uint32_t xrow = keep(sb + own_planes + (16 * warp + (lane >> 2)) * 16 + (lane & 3) * PLANE);
        const uint32_t dx = ((sb + OFF_X) & 0x3FFFF) >> 4;
        const uint32_t da = (((sb + OFF_WS + (warp >> 2) * 8192) & 0x3FFFF) >> 4) | 0x10000u;
        mbar_wait(bars + BAR_X, 0);
        for (int sv = -1; sv < kNSEG; sv++) {
            const int s = __reduce_max_sync(~0u, sv);
            if (LIKELY(s + 1 < kNSEG)) {
                const uint32_t xdst = xrow + ((s + 1) % 3) * SLOT;
                float acc[16];
                uint32_t d0 = (dx + ((s + 1) & 1) * 2048) | 0x10000u;
                asm volatile("" : "+r"(d0));
                sched_fence();
                asm volatile("{.reg .pred p; setp.gt.s32 p, %0, 0; @p bar.sync 8, 384;}" :: "r"(s) : "memory");
                wgmma_fence();
#pragma unroll
                for (int i = 0; i < 32; i++) {
                    const int j = i - SSPOS;
                    const bool ss = j >= 0 && j % SSGAP == 0 && j / SSGAP < 4;
                    const int before = j < 0 ? 0 : min(4, (j + SSGAP - 1) / SSGAP);
                    const int kk = ss ? j / SSGAP : 4 + i - before;
                    const uint64_t db = desc_k128(d0 + (kk >> 2) * 256 + (kk & 3) * 2);
                    const uint32_t (&f)[4] = W[ss ? 0 : kk - 4];
                    if (ss) { if (i == 0) wgmma_ss32<1>(acc, desc_k128(da), db); else wgmma_ss32<0>(acc, desc_k128(da + kk * 128), db); }
                    else if (i == 0) wgmma_rs32_first(acc, f[0], f[1], f[2], f[3], db);
                    else wgmma_rs32<1>(acc, f[0], f[1], f[2], f[3], db);
                    if (i % GRP == GRP - 1) { wgmma_commit(); if (i < 31) wgmma_wait<GDEP>(); }
                }
                wgmma_wait<0>();
                if (warp == 0 && s >= 0) STAMP(1);
                sts128(xdst, pack_bf16(acc[0], acc[1]), pack_bf16(acc[4], acc[5]), pack_bf16(acc[8], acc[9]), pack_bf16(acc[12], acc[13]));
                sts128(xdst + 128, pack_bf16(acc[2], acc[3]), pack_bf16(acc[6], acc[7]), pack_bf16(acc[10], acc[11]), pack_bf16(acc[14], acc[15]));
            }
            __syncwarp();
            mbar_arrive_if(bars + BAR_PL, lead);
            if (LIKELY(s >= 0)) {
                float c[2][4] = {{0.f, 0.f, 0.f, 0.f}, {0.f, 0.f, 0.f, 0.f}};
                constexpr int LA = 2;
                uint32_t b[LA + 1][4];
                bar_sync<1, 384>();
#pragma unroll
                for (int m = -LA; m < 16; m++) {
                    const int l = m + LA;
                    if (l < 16) {
                        ldsm4t(b[l % (LA + 1)], lin + (sb + OFF_MEMT + l * 512));
                        if (l == LA - 1) { sched_fence(); if (warp == 0) STAMP(3); }
                    }
                    if (m >= 0) {
                        const uint32_t (&f0)[4] = m < 2 ? ws[(2 * m) & 3] : W[m < 2 ? 0 : 2 * m - 4];
                        const uint32_t (&f1)[4] = m < 2 ? ws[(2 * m + 1) & 3] : W[m < 2 ? 0 : 2 * m - 3];
                        mma16v(c[0], f0[0], f0[1], f0[2], f0[3], b[m % (LA + 1)][0], b[m % (LA + 1)][1]);
                        mma16v(c[1], f1[0], f1[1], f1[2], f1[3], b[m % (LA + 1)][2], b[m % (LA + 1)][3]);
                    }
                }
                const float inv = __uint_as_float(lds32(bars + OFF_INV + (s & 1) * 4));
                const uint32_t w0 = pack_bf16((c[0][0] + c[1][0]) * inv, (c[0][1] + c[1][1]) * inv);
                const uint32_t w1 = pack_bf16((c[0][2] + c[1][2]) * inv, (c[0][3] + c[1][3]) * inv);
                st_async32(rA + mdst, w0, rA + hbar);
                st_async32(rA + mdst + 128, w1, rA + hbar);
                sts32(sb + mdst, w0); sts32(sb + mdst + 128, w1);
                __syncwarp();
                mbar_arrive_if(bars + BAR_SENT, lead);
                if (rank != 0) {
                    if (O_K2 && rank == 1 && s + 1 < kNSEG) mbar_wait(bars + BAR_SENT, s & 1);
                    st_async32(rB + mdst, w0, rB + hbar);
                    st_async32(rB + mdst + 128, w1, rB + hbar);
                    mdst += s % 3 == 2 ? -2 * SLOT : SLOT;
                } else {
                    asm volatile("{.reg .pred p; setp.ne.u32 p, %2, 0; @p st.async.shared::cluster.mbarrier::complete_tx::bytes.b32 [%0], 0, [%1];}"
                                 :: "r"(rB + OFF_BAR + BAR_DUMMY), "r"(rB + OFF_BAR + BAR_HOP), "r"((uint32_t)lead) : "memory");
                }
                if (warp == 0) STAMP(6);
                if (warp == 1 && rank != 2) {
                    const uint32_t g0 = make_stamp(gtime(), s);
                    STAMP(0);
                    if (lane < 16)
                        asm volatile("st.relaxed.gpu.global.u16 [%0], %1;" :: "l"((uint16_t*)(g_ts + lane * 256 + (s & 1) * 32 + head) + rank), "h"((uint16_t)g0) : "memory");
                    __syncwarp();
                }
            }
            if (s + 1 == kNSEG) break;
            if (s < 0) cluster_signal(1);
            if ((warp & 3) == 0) {
                if (s >= 0) mbar_wait(bars + BAR_SENT, s & 1);
                else { mbar_wait(bars + BAR_C, 0); mbar_wait(bars + BAR_PL, 0); fence_async(); }
                if (warp == 4 && rank != 0) wait_until(clk32() + tune.xp);
                if (lead) send_planes(s + 1, warp >> 2);
                __syncwarp();
            } else if (s >= 0 && (warp == 2 || warp >= 5)) {
                mbar_wait(bars + BAR_HOP, s & 1);
                if (rank != 2) mbar_wait(bars + BAR_HV, s & 1);
                if (warp == 5) {
                    mbar_wait(bars + BAR_KVX + 8 * (s % 3), (s / 3) & 1);
                    if (lead) {
                        mbar_expect(bars + BAR_HOP, hop_bytes);
                        if (rank != 2) mbar_expect(bars + BAR_HV, 2048);
                        mbar_expect(bars + BAR_KVX + 8 * (s % 3), kvx_bytes);
                        if (s + 3 < kNSEG) mbar_expect(bars + BAR_X + 8 * ((s + 1) & 1), 32768);
                    }
                } else if (s + 3 < kNSEG) {
                    const int kb = rank + (warp == 2 ? 0 : (warp - 5) * 3);
                    if (lead && kb < 8) tma5d_mc(sb + OFF_X + ((s + 1) & 1) * 32768 + kb * 4096, &mapx, kb * 64, s + 3, bars + BAR_X + 8 * ((s + 1) & 1), 7);
                }
                __syncwarp();
            }
            if (s + 2 < kNSEG) mbar_wait(bars + BAR_X + 8 * (s & 1), ((s + 2) >> 1) & 1);
            if (s >= 0) {
                if (warp == 3) {
                    mbar_wait(bars + BAR_SENT, s & 1);
                    next_scale(bars, s, lane);
                    if (rank != 2) bar_arrive<4, 160>();
                }
            } else if (warp == 7) {
                mbar_wait(bars + BAR_C + 8, 0);
                if (lead) load_x(sb, &mapx, rank, 2);
                __syncwarp();
            }
        }
    } else {
        asm volatile("setmaxnreg.inc.sync.aligned.u32 184;");
        const int a = warp - 8;
        const int tt = tid - 256;
        if (tt == 0) TL(blockIdx.x, 14);
        auto publish = [&](float ss) {
#pragma unroll
            for (int o = 16; o; o >>= 1) ss += __shfl_xor_sync(~0u, ss, o);
            sts32(bars + OFF_XB + 32 + a * 4, __float_as_uint(ss));
            bar_sync<5, 128>();
            if (tt == 0) {
                const float4 s4 = lds128f(bars + OFF_XB + 32), m4 = lds128f(bars + OFF_XB + 48);
                asm volatile("st.relaxed.gpu.global.v2.u32 [%0], {%1, %2};" :: "l"(&g_stat[blockIdx.x]),
                             "r"(__float_as_uint((s4.x + s4.y) + (s4.z + s4.w)) | 0x80000000u),
                             "r"(__float_as_uint(fmaxf(fmaxf(m4.x, m4.y), fmaxf(m4.z, m4.w))) | 0x80000000u) : "memory");
                TL(blockIdx.x, 8);
            }
            __syncwarp();
        };
        uint32_t w[4][4];
        {
            uint32_t m = 0, xm = 0;
#pragma unroll
            for (int i = 0; i < 4; i++)
#pragma unroll
                for (int q = 0; q < 4; q++) {
                    const uint32_t lo = (i & 2) ? m0[2 * q].y : m0[2 * q].x, hi = (i & 2) ? m0[2 * q + 1].y : m0[2 * q + 1].x;
                    w[i][q] = __byte_perm(lo, hi, (i & 1) ? 0x7632 : 0x5410);
                    m = absmax2(m, w[i][q]);
                }
#pragma unroll
            for (int i = 0; i < 16; i++) xm = absmax2(absmax2(absmax2(absmax2(xm, xs[i].x), xs[i].y), xs[i].z), xs[i].w);
            put_max(bars, a, m);
            put_max(bars + OFF_XB + 48 - OFF_WMAX, a, xm);
        }
        auto first_stage = [&]() {
            mbar_wait(bars + BAR_C, 0);
#pragma unroll
            for (int i = 0; i < 4; i++) sts128(sb + OFF_MEMT + (tt * 4 + i) * 16, w[i][0], w[i][1], w[i][2], w[i][3]);
            bar_arrive<1, 384>();
            if (tt == 0) TL(blockIdx.x, 9);
        };
        auto gather_stats = [&]() {
            if (a == 0) {
                int n = 0; unsigned v;
                do { asm volatile("ld.acquire.gpu.global.u32 %0, [%1];" : "=r"(v) : "l"(&g_ctr[0]) : "memory"); spin_guard(n); } while (v < 32);
                uint2 q0, q1, q2;
                do {
                    q0 = ld_relaxed64(&g_stat[lane * 3]); q1 = ld_relaxed64(&g_stat[lane * 3 + 1]); q2 = ld_relaxed64(&g_stat[lane * 3 + 2]);
                    spin_guard(n);
                } while (!__all_sync(~0u, (q0.x & q0.y & q1.x & q1.y & q2.x & q2.y) >> 31));
                float so = fabsf(__uint_as_float(q0.x)) + fabsf(__uint_as_float(q1.x)), sv = fabsf(__uint_as_float(q2.x));
#pragma unroll
                for (int o = 16; o; o >>= 1) { so += __shfl_xor_sync(~0u, so, o); sv += __shfl_xor_sync(~0u, sv, o); }
                float ro, rv;
                asm("sqrt.approx.f32 %0, %1;" : "=f"(ro) : "f"(so)); asm("sqrt.approx.f32 %0, %1;" : "=f"(rv) : "f"(sv));
                sts32(bars + OFF_CW, __float_as_uint(ro * rv * 24.f));
                sts64f(bars + OFF_XB + lane * 8, fabsf(__uint_as_float(q0.y)), fabsf(__uint_as_float(q1.y)));
                if (tt == 0) TL(blockIdx.x, 10);
                __syncwarp();
            }
            first_stage();
            mbar_wait(bars + BAR_C + 8, 0);
        };
        const uint32_t lin = keep(lane * 16);
        auto stamps = [&](int s) { return (const uint32_t*)((const char*)g_ts + adr(lin >> 2, ((head & 3) * 4 + a) * 1024 + (s & 1) * 128)); };
        uint32_t seen, tsent, gsent;
        uint32_t o42 = keep(((lane >> 3) * kLine + (lane & 7) * 16) | (((4 + (lane >> 4)) * kLine + (lane & 15) * 8) << 16));
        auto collect = [&](int s, auto hasf, auto between) {
            const int ca = (a + blockIdx.x) & 3;
            const char* src = g_ring + slot_off(s + 1) + ca * 4 * kBlkBytes;
            asm volatile("" : "+r"(o42));
            const char* src2 = src + (o42 >> 16);
            src += o42 & 0xFFFF;
            asm volatile("" : "+l"(src), "+l"(src2));
            const uint32_t tref = latest_stamp(stamps(s), seen, tsent, make_stamp(gsent, s));
            wait_until(tref + tune.x[0]);
            if (a == 0) STAMP(4);
            const uint32_t m = stage_blocks<decltype(hasf)::value>(src, src2, adr(lin, sb + ca * 2048) + OFF_MEMT, sb, s + 1, between);
            STAMP(13);
            put_max(bars, a, m);
            if (a == 1 && lane < 8 && s >= 1) *(float4*)(g_ring + slot_off(s) + blockIdx.x * kLine + lane * 16) = make_float4(0.f, 0.f, 0.f, 0.f);
            if (a == 0 && lane == 0 && s == 1) {
                g_stat[blockIdx.x] = make_uint2(0u, 0u);
                if (blockIdx.x == 0) g_ctr[0] = 0;
            }
            __syncwarp();
        };
        auto wait_sent = [&](int s) {
            if (a == 2) {
                mbar_wait(bars + BAR_PL, (s + 1) & 1);
                fence_async();
            }
            mbar_arrive_if(bars + BAR_SENT, lin == 0);
            mbar_wait(bars + BAR_SENT, s & 1);
            tsent = clk32();
            gsent = gtime();
            if (rank == 2 && tt == 0 && (s < 3 || s == 63)) { TL(blockIdx.x, 3 + min(s, 3)); TL(blockIdx.x - 1, 3 + min(s, 3)); TL(blockIdx.x - 2, 3 + min(s, 3)); }
        };

        if (rank != 2) {
            uint32_t WO[3][8][4];
            {
                const int j = lane >> 3, r8 = lane & 7;
                const uint32_t base = sb + OFF_WOST + (a >> 1) * 16384 + ((j >> 1) * 8 + r8) * 128;
                if (tt == 0) TL(blockIdx.x, 11);
                mbar_wait(bars + BAR_WO, 0);
                if (tt == 0) TL(blockIdx.x, 12);
                uint32_t w2[2][8][4];
                float ss = 0.f;
#pragma unroll
                for (int jt = 0; jt < 2; jt++)
#pragma unroll
                    for (int kk = 0; kk < 8; kk++) {
                        const uint32_t o = ((a ^ (kk >> 1)) * 2 + (kk & 1)) * 2048 + ((((a & 1) * 4 + jt * 2 + (j & 1)) ^ r8) << 4);
                        ldsm4t(WO[jt][kk], base + (head & 1) * 32768 + o);
                        ldsm4t(w2[jt][kk], base + (~head & 1) * 32768 + o);
                    }
                asm volatile("" :: "r"(w2[1][7][3]) : "memory");
                bar_sync<5, 128>();
#pragma unroll
                for (int jt = 0; jt < 2; jt++)
#pragma unroll
                    for (int kk = 0; kk < 8; kk++) {
                        if (jt == 0) { WO[2][kk][0] = w2[0][kk][0]; WO[2][kk][1] = w2[0][kk][1]; WO[2][kk][2] = w2[0][kk][2]; WO[2][kk][3] = w2[0][kk][3]; }
                        else sts128(sb + OFF_WO2 + a * 512 + kk * 2048 + lane * 16, w2[jt][kk][0], w2[jt][kk][1], w2[jt][kk][2], w2[jt][kk][3]);
                        ss += sumsq8(WO[jt][kk], w2[jt][kk]);
                    }
                publish(ss);
            }
            gather_stats();
            mbar_wait(bars + BAR_PL, 1);
            const uint32_t qln = keep((((lane >> 3) & 1) * 16 + (lane >> 4) * 8 + (lane & 7)) * 16);
            const uint32_t vln = keep(((lane >> 4) * 8 + (lane & 7)) * 16 + ((a ^ (lane >> 3)) & 1) * PLANE);
            uint32_t ua[4];
#pragma unroll
            for (int j = 0; j < 4; j++) ua[j] = __reduce_max_sync(~0u, sb + (a ^ j) * 512);
            uint32_t slot = 0;
            uint32_t kx[4][4], vf[4][4], w2[8][4];
            auto load_w2 = [&](int k0, int k1) {
#pragma unroll
                for (int kk = k0; kk < k1; kk++) lds128(w2[kk], adr(lin, ua[0]) + (OFF_WO2 + kk * 2048));
            };
            load_w2(0, O_R);
            auto prefetch_k = [&]() {
#pragma unroll
                for (int j = 0; j < 4; j++) ldsm4t(kx[j], adr(lin, ua[j] + slot + a * PLANE) + OFF_KV);
            };
            auto prefetch_v = [&]() {
#pragma unroll
                for (int p = 0; p < 4; p++) ldsm4(vf[p], adr(vln, ua[0] + slot + ((a ^ p) & 2) * PLANE) + (OFF_KV + 5 * PLANE + (p & 1) * 256));
            };
            mbar_wait(bars + BAR_KVX, 0);
            prefetch_k();
            int s3 = 0;
            for (int s = 0; s + 1 < kNSEG; s++) {
                char* dst = g_ring + slot_off(s + 1) + ((head & 1) * 8 + rank * 4 + a) * kBlkBytes;
                sched_fence();
                if (rank == 1) mbar_wait(bars + BAR_KVX + 8 * s3, (s / 3) & 1);
                wait_sent(s);
                prefetch_v();
                mbar_wait(bars + BAR_HOP, s & 1);
                uint32_t q[4][4], km[4], vm[4];
                ldsm4t(q[0], adr(qln, ua[0]) + OFF_QM);
                if (O_KM == 0) ldsm4t(km, adr(lin, ua[0] + slot) + (OFF_KV + 4 * PLANE));
#pragma unroll
                for (int j = 1; j < 4; j++) {
                    ldsm4t(q[j], adr(qln, ua[j]) + OFF_QM);
                    if (O_KM == j) ldsm4t(km, adr(lin, ua[0] + slot) + (OFF_KV + 4 * PLANE));
                }
                if (SF0) sched_fence();
                if (a == 0) STAMP(8);
                float sa[2][4] = {}, sb2[2][4] = {}, ma[4] = {}, mb[4] = {};
#pragma unroll
                for (int j = 0; j < 4; j++) {
                    mma16(sa[O_SCH ? j & 1 : 0], q[j][0], q[j][1], q[j][2], q[j][3], kx[j][0], kx[j][1]);
                    mma16(sb2[O_SCH ? j & 1 : 0], q[j][0], q[j][1], q[j][2], q[j][3], kx[j][2], kx[j][3]);
                }
                mma16(ma, q[0][0], q[0][1], q[0][2], q[0][3], km[0], km[1]);
                mma16(mb, q[0][0], q[0][1], q[0][2], q[0][3], km[2], km[3]);
                float sc[5][2];
                if (O_SCH) { sc[0][0] = (sa[0][0] + sb2[0][2]) + (sa[1][0] + sb2[1][2]); sc[0][1] = (sa[0][1] + sb2[0][3]) + (sa[1][1] + sb2[1][3]); }
                else { sc[0][0] = sa[0][0] + sb2[0][2]; sc[0][1] = sa[0][1] + sb2[0][3]; }
                sc[4][0] = ma[0] + mb[2]; sc[4][1] = ma[1] + mb[3];
                sts128f(adr(lin, ua[0]) + OFF_SX, sc[0][0], sc[0][1], sc[4][0], sc[4][1]);
                if (O_SCALE) bar_sync<4, 160>(); else bar_sync<5, 128>();
                const float4 x1 = lds128f(adr(lin, ua[1]) + OFF_SX), x2 = lds128f(adr(lin, ua[2]) + OFF_SX), x3 = lds128f(adr(lin, ua[3]) + OFF_SX);
                bool hv = false;
                if (O_HV == 2) hv = mbar_test(bars + BAR_HV, s & 1);
                if (O_HV == 0) { mbar_wait(bars + BAR_HV, s & 1); ldsm4(vm, adr(lin, ua[0] + slot) + (OFF_KV + 9 * PLANE)); }
                sc[1][0] = x1.x; sc[1][1] = x1.y; sc[2][0] = x2.x; sc[2][1] = x2.y; sc[3][0] = x3.x; sc[3][1] = x3.y;
                sc[4][0] = (sc[4][0] + x1.z) + (x2.z + x3.z); sc[4][1] = (sc[4][1] + x1.w) + (x2.w + x3.w);
                float m = fmaxf(fmaxf(fmaxf(sc[0][0], sc[0][1]), fmaxf(sc[1][0], sc[1][1])), fmaxf(fmaxf(sc[2][0], sc[2][1]), fmaxf(sc[3][0], sc[3][1])));
                m = fmaxf(m, fmaxf(sc[4][0], sc[4][1]));
                if (a == 0) STAMP(9);
                if (O_SHF) {
                    const float m1 = __shfl_xor_sync(~0u, m, 1), m2 = __shfl_xor_sync(~0u, m, 2), m3 = __shfl_xor_sync(~0u, m, 3);
                    if (O_HV == 1) { mbar_wait(bars + BAR_HV, s & 1); ldsm4(vm, adr(lin, ua[0] + slot) + (OFF_KV + 9 * PLANE)); }
                    if (O_HV == 2) { mbar_wait_unless(bars + BAR_HV, s & 1, hv); ldsm4(vm, adr(lin, ua[0] + slot) + (OFF_KV + 9 * PLANE)); }
                    m = fmaxf(fmaxf(m, m1), fmaxf(m2, m3));
                } else {
                    m = fmaxf(m, __shfl_xor_sync(~0u, m, 1));
                    const float m2 = __shfl_xor_sync(~0u, m, 2);
                    if (O_HV == 1) { mbar_wait(bars + BAR_HV, s & 1); ldsm4(vm, adr(lin, ua[0] + slot) + (OFF_KV + 9 * PLANE)); }
                    m = fmaxf(m, m2);
                }
                float scale;
                if (O_SCALE) scale = __uint_as_float(lds32(bars + OFF_SCALE));
                load_w2(O_R, O_W0);
                m *= -kScaleLog2;
                uint32_t P[5];
#pragma unroll
                for (int p = 0; p < 5; p++) P[p] = pack_bf16(ex2v(fmaf(sc[p][0], kScaleLog2, m)), ex2v(fmaf(sc[p][1], kScaleLog2, m)));
                uint32_t ob[4][4];
                float rs[3][4] = {};
                if (O_PV == 2) {
                    float oa[4][4] = {};
#pragma unroll
                    for (int i = 0; i < 4; i++) mma8v(oa[i], P[4], P[4], vm[i]);
#pragma unroll
                    for (int i = 0; i < 4; i++) mma16v(oa[i], P[0], P[0], P[1], P[1], vf[i >> 1][(i & 1) * 2], vf[i >> 1][(i & 1) * 2 + 1]);
#pragma unroll
                    for (int i = 0; i < 4; i++) mma16v(oa[i], P[2], P[2], P[3], P[3], vf[2 + (i >> 1)][(i & 1) * 2], vf[2 + (i >> 1)][(i & 1) * 2 + 1]);
#pragma unroll
                    for (int i = 0; i < 4; i++) ob[0][i] = pack_bf16(oa[i][0], oa[i][1]);
                } else if (O_PV == 3) {
                    float oa[4][4] = {};
#pragma unroll
                    for (int p = 0; p < 4; p++)
#pragma unroll
                        for (int i = 0; i < 4; i++) mma8v(oa[i], P[p], P[p], vf[(p & 2) + (i >> 1)][(i & 1) * 2 + (p & 1)]);
#pragma unroll
                    for (int i = 0; i < 4; i++) mma8v(oa[i], P[4], P[4], vm[i]);
#pragma unroll
                    for (int i = 0; i < 4; i++) ob[0][i] = pack_bf16(oa[i][0], oa[i][1]);
                } else if (O_PV == 0) {
                    float oa[4][4] = {};
#pragma unroll
                    for (int i = 0; i < 4; i++) mma16v(oa[i], P[0], P[0], P[1], P[1], vf[i >> 1][(i & 1) * 2], vf[i >> 1][(i & 1) * 2 + 1]);
#pragma unroll
                    for (int i = 0; i < 4; i++) mma16v(oa[i], P[2], P[2], P[3], P[3], vf[2 + (i >> 1)][(i & 1) * 2], vf[2 + (i >> 1)][(i & 1) * 2 + 1]);
#pragma unroll
                    for (int i = 0; i < 4; i++) mma8v(oa[i], P[4], P[4], vm[i]);
#pragma unroll
                    for (int i = 0; i < 4; i++) ob[0][i] = pack_bf16(oa[i][0], oa[i][1]);
                } else {
                    float oa[4][4] = {}, lo[4][4] = {};
#pragma unroll
                    for (int i = 0; i < 4; i++) mma16v(oa[i], P[0], P[2], P[1], P[3], vf[i >> 1][(i & 1) * 2], vf[i >> 1][(i & 1) * 2 + 1]);
#pragma unroll
                    for (int i = 0; i < 4; i++) mma16v(lo[i], P[0], P[2], P[1], P[3], vf[2 + (i >> 1)][(i & 1) * 2], vf[2 + (i >> 1)][(i & 1) * 2 + 1]);
#pragma unroll
                    for (int i = 0; i < 4; i++) mma8v(oa[i], P[4], P[4], vm[i]);
#pragma unroll
                    for (int i = 0; i < 4; i++) ob[0][i] = pack_bf16(oa[i][0] + lo[i][2], oa[i][1] + lo[i][3]);
                }
                sts128(adr(lin, ua[0]) + OFF_OX, ob[0][0], ob[0][1], ob[0][2], ob[0][3]);
                if (O_SEEN == 1) seen = load_stamps(stamps(s));
                if (O_SF1) sched_fence();
                if (O_PV != 1) { mma16v(rs[0], kOnes, kOnes, kOnes, kOnes, P[0], P[1]); mma16v(rs[1], kOnes, kOnes, kOnes, kOnes, P[2], P[3]); }
                else { mma16v(rs[0], kOnes, kOnes, kOnes, kOnes, P[0], P[2]); mma16v(rs[1], kOnes, kOnes, kOnes, kOnes, P[1], P[3]); }
                mma8v(rs[2], kOnes, kOnes, P[4]);
                if (a == 0) STAMP(10);
                if (O_SCALE) bar_sync<5, 128>(); else bar_sync<4, 160>();
#pragma unroll
                for (int o = 1; o < 4; o++) lds128(ob[o], adr(lin, ua[o]) + OFF_OX);
                if (!O_SCALE) scale = __uint_as_float(lds32(bars + OFF_SCALE));
                load_w2(O_W0, O_W1);
                const float i0 = rcp((rs[0][0] + rs[1][0]) + rs[2][0]) * scale, i1 = rcp((rs[0][1] + rs[1][1]) + rs[2][1]) * scale;
                float c[4][2][4] = {};
                auto tile = [&](int jt, int k0, int k1) {
#pragma unroll
                    for (int kk = k0; kk < k1; kk++) {
                        const uint32_t (&f)[4] = jt < 3 ? WO[jt % 3][kk] : w2[kk];
                        mma16v(c[jt][kk & 1], f[0], f[1], f[2], f[3], ob[kk >> 1][(kk & 1) * 2], ob[kk >> 1][(kk & 1) * 2 + 1]);
                    }
                };
                auto reduce = [&](int jp) {
                    const int adv = jp == 0 ? 0 : ((head & 1) ? -8 * kBlkBytes : 8 * kBlkBytes);
                    uint32_t h[4];
#pragma unroll
                    for (int i = 0; i < 4; i++) {
                        const float (&u0)[4] = c[2 * jp + (i >> 1)][0]; const float (&u1)[4] = c[2 * jp + (i >> 1)][1];
                        h[i] = pack_f16((u0[(i & 1) * 2] + u1[(i & 1) * 2]) * i0, (u0[(i & 1) * 2 + 1] + u1[(i & 1) * 2 + 1]) * i1);
                    }
                    red_h128(dst + adv + (o42 & 0xFFFF), h[0], h[1], h[2], 0x3C00u);
                    red_h64(dst + adv + (o42 >> 16), h[3], 0x3C00u);
                };
                tile(0, 0, 8); tile(1, 0, 8);
                tile(2, 0, O_T2); tile(3, 0, O_T3);
                if (O_SEEN == 0) seen = load_stamps(stamps(s));
                if (O_SF2) sched_fence();
                tile(2, O_T2, O_T2 + O_T2B);
                reduce(0);
                sched_fence();
                if (a == 0) STAMP(12);
                load_w2(O_W1, 8);
                tile(2, O_T2 + O_T2B, 8); tile(3, O_T3, 8);
                if (O_REL) {
                    sched_fence();
                    asm volatile("{.reg .pred p; setp.lt.s32 p, %0, %1; @p bar.arrive 8, 384;}" :: "r"(s), "n"(kNSEG - 2) : "memory");
                    if (O_REL == 2) sched_fence();
                }
                reduce(1);
                if (!O_REL && s + 2 < kNSEG) bar_arrive<8, 384>();
                if (a == 0) STAMP(11);
                if (++s3 == 3) s3 = 0;
                slot = s3 * SLOT;
                if (rank == 0) mbar_wait(bars + BAR_KVX + 8 * s3, ((s + 1) / 3) & 1);
                prefetch_k();
                sched_fence();
                collect(s, Flag<false>(), []() {});
            }
            mbar_wait(bars + BAR_HOP, 1);
            mbar_wait(bars + BAR_HV, 1);
        } else {
            if (a == 3) {
                if (lane == 0) asm volatile("fence.acq_rel.gpu; red.relaxed.gpu.global.add.u32 [%0], 1;" :: "l"(&g_ctr[0]) : "memory");
                __syncwarp();
                asm volatile("griddepcontrol.launch_dependents;" ::: "memory");
                if (lane == 0) TL(blockIdx.x, 16);
            }
            bar_sync<3, 384>();
            publish(lane < 2 ? __uint_as_float(lds32(bars + OFF_XB + (2 * a + lane) * 4)) : 0.f);
            gather_stats();
            const int u = a & 1;
            const uint32_t xown = sb + OFF_SX + a * 2560 + lane * 16, xoth = sb + OFF_SX + (a ^ 1) * 2560 + lane * 16;
            const uint32_t ost = sb + OFF_OST + a * 2048;
            int s3 = 0;
            for (int s = 0; s < kNSEG; s++) {
                const uint32_t slot = sb + OFF_KV + s3 * SLOT + u * 1024;
                const uint32_t lins = slot + lin, par = slot + ((lane >> 3) & 1) * PLANE + ((lane >> 4) * 8 + (lane & 7)) * 16;
                const uint32_t qad = slot + (10 + (((lane >> 3) & 1) ? 3 - (a >> 1) : (a >> 1))) * PLANE + ((lane >> 4) * 8 + (lane & 7)) * 16;
                mbar_wait(bars + BAR_KVX + 8 * s3, (s / 3) & 1);
                wait_sent(s);
                if (a == 3) STAMP(8);
                auto wait_mem = [&]() { mbar_wait(bars + BAR_HOP, s & 1); };
                if (a < 2) x_attention<0>(lins, par, qad, xown, xoth, lane, ost, wait_mem, stamps(s), seen, s + 2 < kNSEG);
                else x_attention<1>(lins, par, qad, xown, xoth, lane, ost, wait_mem, stamps(s), seen, s + 2 < kNSEG);
                if (a == 3) STAMP(11);
                if (a == 0) STAMP(12);
                if (s + 1 == kNSEG) break;
                auto store_o = [&]() {
                    if (lane == 0) {
#pragma unroll
                        for (int i = 0; i < 2; i++)
                            asm volatile("cp.async.bulk.tensor.2d.global.shared::cta.bulk_group [%0, {%2, %3}], [%1];"
                                         :: "l"(&mapos), "r"(ost + i * 1024), "r"(head * kDH + u * 64), "r"(s * 32 + (i ? 3 - (a >> 1) : (a >> 1)) * 8) : "memory");
                        asm volatile("cp.async.bulk.commit_group;" ::: "memory");
                    }
                    __syncwarp();
                };
                fence_async();
                __syncwarp();
                if (++s3 == 3) s3 = 0;
                collect(s, Flag<true>(), store_o);
                announce(&g_oflag[s * 8 + (head >> 2)], lane == 0);
            }
            __syncwarp();
#pragma unroll
            for (int i = 0; i < 4; i++) {
                const int row = i * 4 + (lane >> 3);
                uint32_t r[4];
                lds128(r, ost + row * 128 + (((lane & 7) ^ (row & 7)) << 4));
                *(uint4*)(g_O + (size_t)(kS - 32 + (i < 2 ? (a >> 1) : 3 - (a >> 1)) * 8 + (row & 7)) * kHD + head * kDH + u * 64 + (lane & 7) * 8) = make_uint4(r[0], r[1], r[2], r[3]);
            }
            __syncwarp();
            if (lane == 0) asm volatile("fence.acq_rel.gpu; red.relaxed.gpu.global.add.u32 [%0], 1;" :: "l"(&g_oflag[(kNSEG - 1) * 8 + (head >> 2)]) : "memory");
            __syncwarp();
        }
    }
    cluster_sync();
    if (tid == 0) TL(blockIdx.x, 7);
}

constexpr int SIDE_CTAS = 36, SIDE_THREADS = 384;
constexpr int S_RED = 131072;
constexpr int S_KV = S_RED + 16384;
constexpr int S_BAR = S_KV + 1280;
constexpr int SIDE_SMEM = S_BAR + 272;
constexpr int SB_FULL = 136, SB_EMPTY = 32, SB_W = 64, SB_RED = 72, SB_ACK = 104;

DI void tma5d(uint32_t dst, const CUtensorMap* m, int c0, int c4, uint32_t bar) {
    asm volatile("cp.async.bulk.tensor.5d.shared::cluster.global.mbarrier::complete_tx::bytes [%0], [%1, {%3, %5, %5, %5, %4}], [%2];"
                 :: "r"(dst), "l"(m), "r"(bar), "r"(c0), "r"(c4), "r"(0) : "memory");
}
DI void wait_count(const unsigned* p, unsigned target) {
    int n = 0; unsigned v;
    while (true) {
        asm volatile("ld.acquire.gpu.global.u32 %0, [%1];" : "=r"(v) : "l"(p) : "memory");
        if (v >= target) break;
        spin_guard(n);
        if (NSLEEP) __nanosleep(NSLEEP);
    }
}
DI void signal(unsigned* p) { asm volatile("fence.acq_rel.gpu; red.relaxed.gpu.global.add.u32 [%0], 1;" :: "l"(p) : "memory"); }
DI void stage_weights(uint32_t sb, const CUtensorMap* m, int col, int row) {
    mbar_expect(sb + S_BAR + SB_W, 131072);
    for (int i = 0; i < 4; i++) tma2d(sb + i * 32768, m, col + (i & 1) * 64, row + (i >> 1) * 256, sb + S_BAR + SB_W);
}
DI void load_weights(uint32_t (&W)[32][4], uint32_t sb, int warp, int lane, bool perm) {
    const int j = lane >> 3;
#pragma unroll
    for (int kk = 0; kk < 32; kk++) {
        const int p = (kk & 1) * 16 + (j >> 1) * 8 + (lane & 7);
        const int r = perm ? (((p >> 1) & 3) << 3) | (((p >> 3) & 3) << 1) | (p & 1) : p;
        ldsm4t(W[kk], sb + ((kk >> 4) * 2 + (warp >> 2)) * 32768 + (((kk >> 1) & 7) * 32 + r) * 128 + ((((warp & 3) * 2 + (j & 1)) ^ (r & 7)) << 4));
    }
}
constexpr int NQ = NQDEF;
DI void proj_tokens(float (&acc)[16], const uint32_t (&W)[32][4], uint32_t d0, uint32_t full, uint32_t parity) {
#pragma unroll
    for (int kk = 0; kk < 32; kk++) {
        if (kk % (32 / NQ) == 0) mbar_wait(full + kk / (32 / NQ) * 32, parity);
        if (kk == 0) { wgmma_fence(); wgmma_rs32_first(acc, W[0][0], W[0][1], W[0][2], W[0][3], desc_k128(d0)); }
        else wgmma_rs32<1>(acc, W[kk][0], W[kk][1], W[kk][2], W[kk][3], desc_k128(d0 + (kk >> 2) * 256 + (kk & 3) * 2));
    }
    wgmma_commit();
    wgmma_wait<0>();
}
DI float phi(float t) { return (t > 0.f ? t + 1.f : ex2(t * 1.4426950408889634f)) + 1e-6f; }

__global__ void __launch_bounds__(SIDE_THREADS, 1)
side_kernel(const __grid_constant__ CUtensorMap mapx, const __grid_constant__ CUtensorMap mapw, const __grid_constant__ CUtensorMap mapwoa,
            const __grid_constant__ CUtensorMap mapwob, const __grid_constant__ CUtensorMap mapO, const __grid_constant__ CUtensorMap mapob,
            const __nv_bfloat16* __restrict__ xg, const __nv_bfloat16* __restrict__ gw, const __grid_constant__ CUtensorMap mapout) {
    extern __shared__ __align__(1024) unsigned char smem[];
    const uint32_t sb = smem_u32(smem), bars = sb + S_BAR;
    const int tid = threadIdx.x, lane = tid & 31, cta = blockIdx.x;
    const int warp = __reduce_max_sync(~0u, tid >> 5);
    const int cb = cta % 12, third = cta / 12;
    const int seg0 = third == 0 ? 0 : 1 + 21 * third, nseg1 = third == 0 ? 22 : 21;
    const bool fin = cta >= 32;
    const int kb = cta >> 2, nb = cta & 3;
    const uint32_t dx = ((sb & 0x3FFFF) >> 4) | 0x10000u;

    if (tid == 0) {
        for (int i = 0; i < 4; i++) mbar_init(bars + SB_EMPTY + 8 * i, 2);
        for (int i = 0; i < 4 * NQ; i++) mbar_init(bars + SB_FULL + 8 * i, 1);
        mbar_init(bars + SB_W, 1);
        for (int i = 0; i < 4; i++) { mbar_init(bars + SB_RED + 8 * i, fin ? 1 : 8); mbar_init(bars + SB_ACK + 8 * i, fin ? 8 : 1); }
        asm volatile("fence.mbarrier_init.release.cluster;" ::: "memory");
        stage_weights(sb, &mapw, cb * 128, 0);
        TLS(96 + cta, 0);
    }
    __syncthreads();

    if (warp < 8) {
        asm volatile("setmaxnreg.inc.sync.aligned.u32 224;");
        uint32_t W[32][4];
        const int g = lane >> 2, t = lane & 3;
        const bool lead = (tid & 127) == 0;
        mbar_wait(bars + SB_W, 0);
        load_weights(W, sb, warp, lane, false);
        bar_sync<1, 288>();
        if (tid == 0) TLS(96 + cta, 1);
        for (int it = 0; it < nseg1; it++) {
            float acc[16];
            proj_tokens(acc, W, dx + (it & 3) * 2048, bars + SB_FULL + 8 * (it & 3), (it >> 2) & 1);
            mbar_arrive_if(bars + SB_EMPTY + 8 * (it & 3), lead);
            if (cb < 8) {
#pragma unroll
                for (int i = 0; i < 16; i++) acc[i] = phi(acc[i]);
            }
            __nv_bfloat16* dst = g_qkvT + (size_t)(cb * 128 + warp * 16 + g) * kS + (seg0 + it) * 32 + t * 8;
            *(uint4*)dst = make_uint4(pack_bf16(acc[0], acc[1]), pack_bf16(acc[4], acc[5]), pack_bf16(acc[8], acc[9]), pack_bf16(acc[12], acc[13]));
            *(uint4*)(dst + 8 * kS) = make_uint4(pack_bf16(acc[2], acc[3]), pack_bf16(acc[6], acc[7]), pack_bf16(acc[10], acc[11]), pack_bf16(acc[14], acc[15]));
        }
        bar_sync<1, 288>();
        if (tid == 0) { TLS(96 + cta, 2); signal(&g_sync[0]); if (!fin) wait_count(&g_sync[0], SIDE_CTAS); TLS(96 + cta, 3); }
        bar_sync<2, 256>();
        if (!fin) {
            const __nv_bfloat16* pk = g_qkvT + (size_t)(512 + cta * 16 + g) * kS + warp * 256 + t * 8;
            float c[3][4] = {};
#pragma unroll 2
            for (int i = 0; i < 8; i++) {
                const uint4 k0 = __ldcg((const uint4*)(pk + i * 32)), k1 = __ldcg((const uint4*)(pk + 8 * kS + i * 32));
                const uint4 v0 = __ldcg((const uint4*)(pk + 512 * kS + i * 32)), v1 = __ldcg((const uint4*)(pk + 520 * kS + i * 32));
                mma16(c[0], k0.x, k1.x, k0.y, k1.y, v0.x, v0.y); mma16(c[1], k0.x, k1.x, k0.y, k1.y, v1.x, v1.y); mma16(c[2], k0.x, k1.x, k0.y, k1.y, kOnes, kOnes);
                mma16(c[0], k0.z, k1.z, k0.w, k1.w, v0.z, v0.w); mma16(c[1], k0.z, k1.z, k0.w, k1.w, v1.z, v1.w); mma16(c[2], k0.z, k1.z, k0.w, k1.w, kOnes, kOnes);
            }
#pragma unroll
            for (int i = 0; i < 3; i++) sts128f(sb + S_RED + (warp * 3 + i) * 512 + lane * 16, c[i][0], c[i][1], c[i][2], c[i][3]);
            bar_sync<2, 256>();
            if (tid < 96) {
                float4 a4 = make_float4(0.f, 0.f, 0.f, 0.f);
#pragma unroll
                for (int w = 0; w < 8; w++) { const float4 b4 = lds128f(sb + S_RED + w * 1536 + tid * 16); a4.x += b4.x; a4.y += b4.y; a4.z += b4.z; a4.w += b4.w; }
                if (warp < 2) {
                    sts64f(sb + S_KV + g * 80 + (warp * 8 + 2 * t) * 4, a4.x, a4.y);
                    sts64f(sb + S_KV + (g + 8) * 80 + (warp * 8 + 2 * t) * 4, a4.z, a4.w);
                } else if (t == 0) {
                    sts32(sb + S_KV + g * 80 + 64, __float_as_uint(a4.x)); sts32(sb + S_KV + (g + 8) * 80 + 64, __float_as_uint(a4.z));
                }
            }
            bar_sync<2, 256>();
#pragma unroll 1
            for (int i = 0; i < 4; i++) {
                const int tp = i * 256 + tid;
                uint32_t q[16];
#pragma unroll
                for (int d = 0; d < 16; d++) q[d] = __ldcg((const uint32_t*)(g_qkvT + (size_t)(cta * 16 + d) * kS) + tp);
                float n0[17] = {}, n1[17] = {};
#pragma unroll
                for (int d = 0; d < 16; d++) {
                    const float q0 = __uint_as_float(q[d] << 16), q1 = __uint_as_float(q[d] & 0xFFFF0000u);
#pragma unroll
                    for (int e4 = 0; e4 < 4; e4++) {
                        const float4 kv = lds128f(sb + S_KV + d * 80 + e4 * 16);
                        n0[e4 * 4] = fmaf(q0, kv.x, n0[e4 * 4]); n0[e4 * 4 + 1] = fmaf(q0, kv.y, n0[e4 * 4 + 1]);
                        n0[e4 * 4 + 2] = fmaf(q0, kv.z, n0[e4 * 4 + 2]); n0[e4 * 4 + 3] = fmaf(q0, kv.w, n0[e4 * 4 + 3]);
                        n1[e4 * 4] = fmaf(q1, kv.x, n1[e4 * 4]); n1[e4 * 4 + 1] = fmaf(q1, kv.y, n1[e4 * 4 + 1]);
                        n1[e4 * 4 + 2] = fmaf(q1, kv.z, n1[e4 * 4 + 2]); n1[e4 * 4 + 3] = fmaf(q1, kv.w, n1[e4 * 4 + 3]);
                    }
                    const float z = __uint_as_float(lds32(sb + S_KV + d * 80 + 64));
                    n0[16] = fmaf(q0, z, n0[16]); n1[16] = fmaf(q1, z, n1[16]);
                }
                const float r0 = 1.f / (n0[16] + 1e-6f), r1 = 1.f / (n1[16] + 1e-6f);
                uint4* d0 = (uint4*)(g_ob + (size_t)(2 * tp) * kD + cta * 16);
#pragma unroll
                for (int hf = 0; hf < 2; hf++) {
                    d0[hf] = make_uint4(pack_bf16(n0[hf * 8] * r0, n0[hf * 8 + 1] * r0), pack_bf16(n0[hf * 8 + 2] * r0, n0[hf * 8 + 3] * r0),
                                        pack_bf16(n0[hf * 8 + 4] * r0, n0[hf * 8 + 5] * r0), pack_bf16(n0[hf * 8 + 6] * r0, n0[hf * 8 + 7] * r0));
                    d0[kD / 8 + hf] = make_uint4(pack_bf16(n1[hf * 8] * r1, n1[hf * 8 + 1] * r1), pack_bf16(n1[hf * 8 + 2] * r1, n1[hf * 8 + 3] * r1),
                                                 pack_bf16(n1[hf * 8 + 4] * r1, n1[hf * 8 + 5] * r1), pack_bf16(n1[hf * 8 + 6] * r1, n1[hf * 8 + 7] * r1));
                }
            }
        }
        bar_sync<2, 256>();
        if (tid == 0) { TLS(96 + cta, 4); signal(&g_sync[32]); }
        mbar_wait(bars + SB_W, 1);
        load_weights(W, sb, warp, lane, !fin);
        bar_sync<1, 288>();
        auto project = [&](float (&acc)[16], int sg) {
            const int it = nseg1 + sg;
            proj_tokens(acc, W, dx + (it & 3) * 2048, bars + SB_FULL + 8 * (it & 3), (it >> 2) & 1);
            mbar_arrive_if(bars + SB_EMPTY + 8 * (it & 3), lead);
        };
        float4* ap = g_acc + (nb * 8 + warp) * 128 + lane;
        if (!fin) {
            for (int sg = 0; sg < kNSEG; sg++, ap += 4096) {
                float acc[16];
                project(acc, sg);
#pragma unroll
                for (int i = 0; i < 4; i++)
                    asm volatile("red.relaxed.gpu.global.add.v4.f32 [%0], {%1,%2,%3,%4};" :: "l"(ap + i * 32), "f"(acc[4 * i]), "f"(acc[4 * i + 1]), "f"(acc[4 * i + 2]), "f"(acc[4 * i + 3]) : "memory");
                if (sg >= 4) mbar_wait(bars + SB_ACK + 8 * (sg & 3), ((sg >> 2) - 1) & 1);
                __syncwarp();
                mbar_arrive_if(bars + SB_RED + 8 * (sg & 3), lane == 0);
                if (tid == 0) TLS(96 + cta, 8 + sg);
            }
        } else {
            float cur[16];
            for (int sg = -1; sg < kNSEG; sg++) {
                float4 a4[4];
                float2 gt[4];
                auto fetch = [&]() {
#pragma unroll
                    for (int i = 0; i < 4; i++) a4[i] = __ldcg(ap + sg * 4096 + i * 32);
                    mbar_arrive_if(bars + SB_ACK + 8 * (sg & 3), lane == 0);
                };
                bool early = false;
                if (sg >= 0) {
#pragma unroll
                    for (int i = 0; i < 4; i++) gt[i] = __ldcg((const float2*)(g_gate + sg * 32 + i * 8 + 2 * t));
                    early = __all_sync(~0u, mbar_test(bars + SB_RED + 8 * (sg & 3), (sg >> 2) & 1));
                    if (early) fetch();
                }
                float nxt[16];
                if (sg + 1 < kNSEG) project(nxt, sg + 1);
                if (sg >= 0 && !early) { mbar_wait(bars + SB_RED + 8 * (sg & 3), (sg >> 2) & 1); fetch(); }
                if (sg >= 0) {
                    uint32_t lo[4], hi[4];
#pragma unroll
                    for (int i = 0; i < 4; i++) {
                        lo[i] = pack_bf16(gt[i].x * a4[i].x + (1.f - gt[i].x) * cur[4 * i], gt[i].y * a4[i].y + (1.f - gt[i].y) * cur[4 * i + 1]);
                        hi[i] = pack_bf16(gt[i].x * a4[i].z + (1.f - gt[i].x) * cur[4 * i + 2], gt[i].y * a4[i].w + (1.f - gt[i].y) * cur[4 * i + 3]);
                    }
                    const uint32_t tile = sb + S_RED + ((sg & 1) * 2 + (warp >> 2)) * 4096;
                    const uint32_t st = tile + lane * 128 + ((((warp & 3) * 2) ^ (lane & 7)) << 4);
                    asm volatile("stmatrix.sync.aligned.m8n8.x4.trans.shared.b16 [%0], {%1,%2,%3,%4};" :: "r"(st), "r"(lo[0]), "r"(lo[1]), "r"(lo[2]), "r"(lo[3]) : "memory");
                    asm volatile("stmatrix.sync.aligned.m8n8.x4.trans.shared.b16 [%0], {%1,%2,%3,%4};" :: "r"(st ^ 16), "r"(hi[0]), "r"(hi[1]), "r"(hi[2]), "r"(hi[3]) : "memory");
                    fence_async();
                    if (lead) asm volatile("cp.async.bulk.wait_group.read 0;" ::: "memory");
                    if (warp < 4) bar_sync<3, 128>(); else bar_sync<4, 128>();
                    if (lead) {
                        asm volatile("cp.async.bulk.tensor.2d.global.shared::cta.bulk_group [%0, {%2, %3}], [%1];"
                                     :: "l"(&mapout), "r"(tile), "r"(nb * 128 + (warp >> 2) * 64), "r"(sg * 32) : "memory");
                        asm volatile("cp.async.bulk.commit_group;" ::: "memory");
                    }
                    __syncwarp();
                    if (tid == 0) TLS(96 + cta, 8 + sg);
                }
#pragma unroll
                for (int i = 0; i < 16; i++) cur[i] = nxt[i];
            }
            if (lead) asm volatile("cp.async.bulk.wait_group 0;" ::: "memory");
        }
    } else {
    asm volatile("setmaxnreg.dec.sync.aligned.u32 56;");
    if (warp == 8) {
        bar_sync<1, 288>();
        if (lane == 0) {
            for (int it = 0; it < nseg1; it++) {
                const uint32_t full = bars + SB_FULL + 8 * (it & 3);
                if (it >= 4) mbar_wait1(bars + SB_EMPTY + 8 * (it & 3), ((it >> 2) - 1) & 1);
                for (int k = 0; k < 8; k++) {
                    if (k % (8 / NQ) == 0) mbar_expect(full + k / (8 / NQ) * 32, 32768 / NQ);
                    tma5d(sb + (it & 3) * 32768 + k * 4096, &mapx, k * 64, seg0 + it, full + k / (8 / NQ) * 32);
                }
            }
        }
        __syncwarp();
        bar_sync<1, 288>();
        if (lane == 0) { if (fin) stage_weights(sb, &mapwob, nb * 128, 0); else stage_weights(sb, &mapwoa, nb * 128, kb * 512); }
        __syncwarp();
        bar_sync<1, 288>();
        if (lane == 0) {
            wait_count(&g_sync[32], 3 * SIDE_CTAS);
            for (int sg = 0; sg < kNSEG; sg++) {
                const int it = nseg1 + sg;
                const uint32_t full = bars + SB_FULL + 8 * (it & 3);
                mbar_wait1(bars + SB_EMPTY + 8 * (it & 3), ((it >> 2) - 1) & 1);
                if (!fin) wait_count(&g_oflag[sg * 8 + kb], 16);
                asm volatile("fence.proxy.async.global;" ::: "memory");
                for (int k = 0; k < 8; k++) {
                    if (k % (8 / NQ) == 0) mbar_expect(full + k / (8 / NQ) * 32, 32768 / NQ);
                    tma2d(sb + (it & 3) * 32768 + k * 4096, fin ? &mapob : &mapO, (fin ? 0 : kb * 512) + k * 64, sg * 32, full + k / (8 / NQ) * 32);
                }
            }
        }
    } else if (warp >= 10) {
        const uint4 w0 = __ldg((const uint4*)gw + lane), w1 = __ldg((const uint4*)gw + 32 + lane);
        auto dot = [](uint32_t a, uint32_t b, float c) {
            return fmaf(__uint_as_float(a << 16), __uint_as_float(b << 16), fmaf(__uint_as_float(a & 0xFFFF0000u), __uint_as_float(b & 0xFFFF0000u), c));
        };
#pragma unroll 2
        for (int tok = cta * 2 + warp - 10; tok < kS; tok += 2 * SIDE_CTAS) {
            const uint4 x0 = __ldg((const uint4*)(xg + (size_t)tok * kD) + lane), x1 = __ldg((const uint4*)(xg + (size_t)tok * kD) + 32 + lane);
            float a = dot(x0.x, w0.x, dot(x0.y, w0.y, dot(x0.z, w0.z, dot(x0.w, w0.w, 0.f)))) + dot(x1.x, w1.x, dot(x1.y, w1.y, dot(x1.z, w1.z, dot(x1.w, w1.w, 0.f))));
#pragma unroll
            for (int o = 16; o; o >>= 1) a += __shfl_xor_sync(~0u, a, o);
            if (lane == 0) g_gate[tok] = 1.f / (1.f + __expf(-a));
        }
        for (int i = cta * 64 + tid - 320; i < kS * kD / 4; i += SIDE_CTAS * 64) g_acc[i] = make_float4(0.f, 0.f, 0.f, 0.f);
        __syncwarp();
        if (lane == 0) signal(&g_sync[32]);
    } else if (lane == 0) {
        for (int sg = 0; sg < kNSEG; sg++) {
            if (!fin) {
                mbar_wait1(bars + SB_RED + 8 * (sg & 3), (sg >> 2) & 1);
                mbar_arrive(bars + SB_ACK + 8 * (sg & 3));
                signal(&g_done[sg * 4 + nb]);
            } else {
                wait_count(&g_done[sg * 4 + nb], 8);
                if (sg >= 4) mbar_wait1(bars + SB_ACK + 8 * (sg & 3), ((sg >> 2) - 1) & 1);
                mbar_arrive(bars + SB_RED + 8 * (sg & 3));
            }
        }
        TL(96 + cta, 5);
        asm volatile("griddepcontrol.wait;" ::: "memory");
    }
    }
}

typedef CUresult (*EncodeFn)(CUtensorMap*, CUtensorMapDataType, cuuint32_t, void*, const cuuint64_t*, const cuuint64_t*,
                             const cuuint32_t*, const cuuint32_t*, CUtensorMapInterleave, CUtensorMapSwizzle,
                             CUtensorMapL2promotion, CUtensorMapFloatOOBfill);

void encode(EncodeFn fn, CUtensorMap* m, const void* p, int rank, const cuuint64_t* dims, const cuuint64_t* strides, const cuuint32_t* box) {
    const cuuint32_t es[5] = {1, 1, 1, 1, 1};
    fn(m, CU_TENSOR_MAP_DATA_TYPE_BFLOAT16, rank, const_cast<void*>(p), dims, strides, box, es, CU_TENSOR_MAP_INTERLEAVE_NONE,
       CU_TENSOR_MAP_SWIZZLE_128B, CU_TENSOR_MAP_L2_PROMOTION_L2_256B, CU_TENSOR_MAP_FLOAT_OOB_FILL_NONE);
}

#define XDEF 1560
#define XXDEF 3000
#define XPDEF 400
#define XTDEF 0
Tune h_tune = {{XDEF, 0, 0, 0}, XTDEF, XPDEF, XXDEF, 0};

}

extern "C" void kernel_launch(void* const* d_in, const int* in_sizes, int n_in, void* d_out, int out_size) {
    const __nv_bfloat16* x = (const __nv_bfloat16*)d_in[0];
    const __nv_bfloat16* mem0 = (const __nv_bfloat16*)d_in[1];
    const __nv_bfloat16* Wq = (const __nv_bfloat16*)d_in[2];
    const __nv_bfloat16* Wk = (const __nv_bfloat16*)d_in[3];
    const __nv_bfloat16* Wv = (const __nv_bfloat16*)d_in[4];
    const __nv_bfloat16* Wo = (const __nv_bfloat16*)d_in[5];
    const __nv_bfloat16* wqkv = (const __nv_bfloat16*)d_in[8];
    const __nv_bfloat16* wo = (const __nv_bfloat16*)d_in[9];
    const __nv_bfloat16* gw = (const __nv_bfloat16*)d_in[10];
    __nv_bfloat16* out = (__nv_bfloat16*)d_out;

    void* fp = nullptr;
    cudaDriverEntryPointQueryResult qr;
    cudaGetDriverEntryPoint("cuTensorMapEncodeTiled", &fp, cudaEnableDefault, &qr);
    EncodeFn fn = (EncodeFn)fp;
    CUtensorMap mx, mq, mk, mv, mo;
    {
        const cuuint64_t dims[5] = {512, 2, 4, 4, 64}, str[4] = {1024, 8192, 2048, 32768};
        const cuuint32_t box[5] = {64, 2, 4, 4, 1};
        encode(fn, &mx, x, 5, dims, str, box);
    }
    {
        const cuuint64_t dims[2] = {4096, 512}, str[1] = {8192};
        const cuuint32_t box[2] = {64, 64};
        encode(fn, &mq, Wq, 2, dims, str, box); encode(fn, &mk, Wk, 2, dims, str, box); encode(fn, &mv, Wv, 2, dims, str, box);
    }
    {
        const cuuint64_t dims[2] = {512, 4096}, str[1] = {1024};
        const cuuint32_t box[2] = {64, 128};
        encode(fn, &mo, Wo, 2, dims, str, box);
    }
    CUtensorMap mw, mwoa, mwob, mO, mOs, mob, mout;
    {
        const cuuint32_t box[2] = {64, 256}, boxt[2] = {64, 32}, boxs[2] = {64, 8};
        const cuuint64_t d0[2] = {1536, 512}, s0[1] = {3072}, d1[2] = {512, 4096}, s1[1] = {1024}, d2[2] = {512, 512};
        const cuuint64_t d3[2] = {4096, 2048}, s3[1] = {8192}, d4[2] = {512, 2048};
        void *pO, *pob;
        cudaGetSymbolAddress(&pO, g_O); cudaGetSymbolAddress(&pob, g_ob);
        encode(fn, &mw, wqkv, 2, d0, s0, box); encode(fn, &mwoa, Wo, 2, d1, s1, box); encode(fn, &mwob, wo, 2, d2, s1, box);
        encode(fn, &mO, pO, 2, d3, s3, boxt); encode(fn, &mOs, pO, 2, d3, s3, boxs); encode(fn, &mob, pob, 2, d4, s1, boxt);
        encode(fn, &mout, out, 2, d4, s1, boxt);
    }
    void* pr;
    cudaGetSymbolAddress(&pr, g_ring_mem);
    char* ring = (char*)(((uintptr_t)pr + 128 * kLine - 1) & ~(uintptr_t)(128 * kLine - 1)) + h_tune.xq * kLine;
    cudaFuncSetAttribute(chain_kernel, cudaFuncAttributeMaxDynamicSharedMemorySize, CHAIN_SMEM);
    cudaFuncSetAttribute(side_kernel, cudaFuncAttributeMaxDynamicSharedMemorySize, SIDE_SMEM);
    chain_kernel<<<96, 384, CHAIN_SMEM>>>(mx, mq, mk, mv, mo, mOs, mem0, x, ring, h_tune);
    cudaLaunchConfig_t cfg = {};
    cfg.gridDim = dim3(SIDE_CTAS); cfg.blockDim = dim3(SIDE_THREADS); cfg.dynamicSmemBytes = SIDE_SMEM; cfg.stream = 0;
    cudaLaunchAttribute at[1];
    at[0].id = cudaLaunchAttributeProgrammaticStreamSerialization; at[0].val.programmaticStreamSerializationAllowed = 1;
    cfg.attrs = at; cfg.numAttrs = 1;
    cudaLaunchKernelEx(&cfg, side_kernel, mx, mw, mwoa, mwob, mO, mob, x, gw, mout);
}
```
